```python
import torch

def _softmax(x, axis=-1):
    return torch.softmax(x, dim=axis)
def _gelu(x):
    return torch.nn.functional.gelu(x, approximate="tanh")
def _silu(x):
    return torch.nn.functional.silu(x)
def _sigmoid(x):
    return torch.sigmoid(x)
def _layernorm(x, axis=-1, eps=1e-5):
    m = x.mean(dim=axis, keepdim=True)
    v = x.var(dim=axis, keepdim=True, unbiased=False)
    return (x - m) / torch.sqrt(v + eps)
def _scatter_add(tgt, idx, src, axis=0):
    return tgt.clone().index_add_(axis, idx, src)
def _segment_sum(src, seg, n):
    out = torch.zeros((n,) + src.shape[1:], dtype=src.dtype)
    return out.index_add_(0, seg, src)
def _pad(x, pw):
    flat = tuple(v for pair in reversed(pw) for v in pair)
    return torch.nn.functional.pad(x, flat)

kernel_name = 'parallel_sum__ssm_conv_s4__mixer_channel_mlp__prompt'

def setup_inputs():

    _w = (lambda a: (lambda t: t.to(torch.bfloat16) if t.is_floating_point() else t)(torch.as_tensor(a)))
    def _A_setup():
        B, L, D, N = 1, 2048, 512, 128
        A_re = -(lambda _x: torch.exp(torch.as_tensor(_x)))((lambda *s: torch.randn(*s, dtype=torch.bfloat16) * 3.2)(D, N))
        A_im = torch.pi * (lambda *s: torch.randn(*s, dtype=torch.bfloat16) * 0.05)(D, N)
        B_re = (lambda *s: torch.randn(*s, dtype=torch.bfloat16) * 0.1)(D, N)
        B_im = (lambda *s: torch.randn(*s, dtype=torch.bfloat16) * 0.1)(D, N)
        C_re = (lambda *s: torch.randn(*s, dtype=torch.bfloat16) * 0.1)(D, N)
        C_im = (lambda *s: torch.randn(*s, dtype=torch.bfloat16) * 0.1)(D, N)
        log_dt = (lambda *s: torch.randn(*s, dtype=torch.bfloat16) * 0.05)(D) * 0.5 - 4.0
        Dskip = (lambda *s: torch.randn(*s, dtype=torch.bfloat16) * 0.05)(D)
        return {
            "u": _w((lambda *s: torch.randn(*s, dtype=torch.bfloat16) * 0.05)(B, L, D)),
            "A_re": _w(A_re),
            "A_im": _w(A_im),
            "B_re": _w(B_re),
            "B_im": _w(B_im),
            "C_re": _w(C_re),
            "C_im": _w(C_im),
            "log_dt": _w(log_dt),
            "Dskip": _w(Dskip),
        }
    _A_in = _A_setup()

    def _B_setup():
        B, S, D, F = 1, 2048, 512, 1792
        return {
            "x": _w((lambda *s: torch.randn(*s, dtype=torch.bfloat16) * 0.05)(B, S, D)),
            "w1": _w((lambda *s: torch.randn(*s, dtype=torch.bfloat16) * 1.6)(D, F) * (D ** -0.5)),
            "b1": _w((lambda *s: torch.randn(*s, dtype=torch.bfloat16) * 0.8)(F)),
            "w2": _w((lambda *s: torch.randn(*s, dtype=torch.bfloat16) * 0.05)(F, D) * (F ** -0.5)),
            "b2": _w((lambda *s: torch.randn(*s, dtype=torch.bfloat16) * 0.05)(D)),
        }
    _B_in = _B_setup()

    return {
        "A_u": _A_in["u"],
        "A_A_re": _A_in["A_re"],
        "A_A_im": _A_in["A_im"],
        "A_B_re": _A_in["B_re"],
        "A_B_im": _A_in["B_im"],
        "A_C_re": _A_in["C_re"],
        "A_C_im": _A_in["C_im"],
        "A_log_dt": _A_in["log_dt"],
        "A_Dskip": _A_in["Dskip"],
        "B_x": _B_in["x"],
        "B_w1": _B_in["w1"],
        "B_b1": _B_in["b1"],
        "B_w2": _B_in["w2"],
        "B_b2": _B_in["b2"],
    }

def reference(A_u, A_A_re, A_A_im, A_B_re, A_B_im, A_C_re, A_C_im, A_log_dt, A_Dskip, B_x, B_w1, B_b1, B_w2, B_b2):
    def _A_ref(u, A_re, A_im, B_re, B_im, C_re, C_im, log_dt, Dskip):
        Bsz, L, D = u.shape
        dt = torch.exp(log_dt)[:, None]
        A = A_re + 1j * A_im
        Bc = B_re + 1j * B_im
        Cc = C_re + 1j * C_im
        logdA = dt * A
        dB = dt * Bc
        l = (lambda x, dt: x.to(dt))(torch.arange(L), A_re.dtype)
        P = torch.exp(logdA[:, :, None] * l[None, None, :])
        K = torch.einsum("dn,dnl,dn->dl", Cc, P, dB).real
        L2 = 2 * L
        Kp = _pad(K, ((0, 0), (0, L)))
        up = (lambda x, *d: x.permute(*d))(u, 0, 2, 1)
        up = _pad(up, ((0, 0), (0, 0), (0, L)))
        Kf = (lambda x, axes=(-2,-1): torch.fft.rfft2(x.float(), dim=axes))(Kp[:, None, :], axes=(-2, -1))
        Uf = (lambda x, axes=(-2,-1): torch.fft.rfft2(x.float(), dim=axes))(up[:, :, None, :], axes=(-2, -1))
        Yf = Uf * Kf[None, :, :, :]
        y = (lambda x, s, axes=(-2,-1): torch.fft.irfft2(x, s=s, dim=axes).to(torch.bfloat16))(Yf, (1, L2), axes=(-2, -1))[:, :, 0, :L]
        y = (lambda x, *d: x.permute(*d))(y, 0, 2, 1) + u * Dskip[None, None, :]
        return y

    def _B_ref(x, w1, b1, w2, b2):
        y = _layernorm(x, axis=-1)
        h = _gelu(torch.einsum("bsd,df->bsf", y, w1) + b1)
        return torch.einsum("bsf,fd->bsd", h, w2) + b2

    x = A_u
    xn = _layernorm(x, axis=-1)
    return x + _A_ref(xn, A_A_re, A_A_im, A_B_re, A_B_im, A_C_re, A_C_im, A_log_dt, A_Dskip) + _B_ref(xn, B_w1, B_b1, B_w2, B_b2)
```

```cpp
#include <cuda_runtime.h>
#include <cuda_bf16.h>
#include <cuda.h>
#include <stdint.h>

template <int OFF> __device__ __forceinline__ void wgmma_rs_k128(float* d, uint32_t a0, uint32_t a1, uint32_t a2, uint32_t a3, uint64_t b, int sd) {
    asm volatile("{ .reg .pred p; .reg .b64 db; setp.ne.b32 p, %69, 0; add.s64 db, %68, %70;\n"
        "wgmma.mma_async.sync.aligned.m64n128k16.f32.bf16.bf16 {%0, %1, %2, %3, %4, %5, %6, %7, %8, %9, %10, %11, %12, %13, %14, %15, %16, %17, %18, %19, %20, %21, %22, %23, %24, %25, %26, %27, %28, %29, %30, %31, %32, %33, %34, %35, %36, %37, %38, %39, %40, %41, %42, %43, %44, %45, %46, %47, %48, %49, %50, %51, %52, %53, %54, %55, %56, %57, %58, %59, %60, %61, %62, %63}, {%64, %65, %66, %67}, db, p, 1, 1, 0; }\n"
        : "+f"(d[0]), "+f"(d[1]), "+f"(d[2]), "+f"(d[3]), "+f"(d[4]), "+f"(d[5]), "+f"(d[6]), "+f"(d[7]), "+f"(d[8]), "+f"(d[9]), "+f"(d[10]), "+f"(d[11]), "+f"(d[12]), "+f"(d[13]), "+f"(d[14]), "+f"(d[15]), "+f"(d[16]), "+f"(d[17]), "+f"(d[18]), "+f"(d[19]), "+f"(d[20]), "+f"(d[21]), "+f"(d[22]), "+f"(d[23]), "+f"(d[24]), "+f"(d[25]), "+f"(d[26]), "+f"(d[27]), "+f"(d[28]), "+f"(d[29]), "+f"(d[30]), "+f"(d[31]), "+f"(d[32]), "+f"(d[33]), "+f"(d[34]), "+f"(d[35]), "+f"(d[36]), "+f"(d[37]), "+f"(d[38]), "+f"(d[39]), "+f"(d[40]), "+f"(d[41]), "+f"(d[42]), "+f"(d[43]), "+f"(d[44]), "+f"(d[45]), "+f"(d[46]), "+f"(d[47]), "+f"(d[48]), "+f"(d[49]), "+f"(d[50]), "+f"(d[51]), "+f"(d[52]), "+f"(d[53]), "+f"(d[54]), "+f"(d[55]), "+f"(d[56]), "+f"(d[57]), "+f"(d[58]), "+f"(d[59]), "+f"(d[60]), "+f"(d[61]), "+f"(d[62]), "+f"(d[63])
        : "r"(a0), "r"(a1), "r"(a2), "r"(a3), "l"(b), "r"(sd), "n"(OFF));
}
template <int OFF> __device__ __forceinline__ void wgmma_rs_k112(float* d, uint32_t a0, uint32_t a1, uint32_t a2, uint32_t a3, uint64_t b, int sd) {
    asm volatile("{ .reg .pred p; .reg .b64 db; setp.ne.b32 p, %61, 0; add.s64 db, %60, %62;\n"
        "wgmma.mma_async.sync.aligned.m64n112k16.f32.bf16.bf16 {%0, %1, %2, %3, %4, %5, %6, %7, %8, %9, %10, %11, %12, %13, %14, %15, %16, %17, %18, %19, %20, %21, %22, %23, %24, %25, %26, %27, %28, %29, %30, %31, %32, %33, %34, %35, %36, %37, %38, %39, %40, %41, %42, %43, %44, %45, %46, %47, %48, %49, %50, %51, %52, %53, %54, %55}, {%56, %57, %58, %59}, db, p, 1, 1, 0; }\n"
        : "+f"(d[0]), "+f"(d[1]), "+f"(d[2]), "+f"(d[3]), "+f"(d[4]), "+f"(d[5]), "+f"(d[6]), "+f"(d[7]), "+f"(d[8]), "+f"(d[9]), "+f"(d[10]), "+f"(d[11]), "+f"(d[12]), "+f"(d[13]), "+f"(d[14]), "+f"(d[15]), "+f"(d[16]), "+f"(d[17]), "+f"(d[18]), "+f"(d[19]), "+f"(d[20]), "+f"(d[21]), "+f"(d[22]), "+f"(d[23]), "+f"(d[24]), "+f"(d[25]), "+f"(d[26]), "+f"(d[27]), "+f"(d[28]), "+f"(d[29]), "+f"(d[30]), "+f"(d[31]), "+f"(d[32]), "+f"(d[33]), "+f"(d[34]), "+f"(d[35]), "+f"(d[36]), "+f"(d[37]), "+f"(d[38]), "+f"(d[39]), "+f"(d[40]), "+f"(d[41]), "+f"(d[42]), "+f"(d[43]), "+f"(d[44]), "+f"(d[45]), "+f"(d[46]), "+f"(d[47]), "+f"(d[48]), "+f"(d[49]), "+f"(d[50]), "+f"(d[51]), "+f"(d[52]), "+f"(d[53]), "+f"(d[54]), "+f"(d[55])
        : "r"(a0), "r"(a1), "r"(a2), "r"(a3), "l"(b), "r"(sd), "n"(OFF));
}
template <int OFF> __device__ __forceinline__ void wgmma_rs_k96(float* d, uint32_t a0, uint32_t a1, uint32_t a2, uint32_t a3, uint64_t b, int sd) {
    asm volatile("{ .reg .pred p; .reg .b64 db; setp.ne.b32 p, %53, 0; add.s64 db, %52, %54;\n"
        "wgmma.mma_async.sync.aligned.m64n96k16.f32.bf16.bf16 {%0, %1, %2, %3, %4, %5, %6, %7, %8, %9, %10, %11, %12, %13, %14, %15, %16, %17, %18, %19, %20, %21, %22, %23, %24, %25, %26, %27, %28, %29, %30, %31, %32, %33, %34, %35, %36, %37, %38, %39, %40, %41, %42, %43, %44, %45, %46, %47}, {%48, %49, %50, %51}, db, p, 1, 1, 0; }\n"
        : "+f"(d[0]), "+f"(d[1]), "+f"(d[2]), "+f"(d[3]), "+f"(d[4]), "+f"(d[5]), "+f"(d[6]), "+f"(d[7]), "+f"(d[8]), "+f"(d[9]), "+f"(d[10]), "+f"(d[11]), "+f"(d[12]), "+f"(d[13]), "+f"(d[14]), "+f"(d[15]), "+f"(d[16]), "+f"(d[17]), "+f"(d[18]), "+f"(d[19]), "+f"(d[20]), "+f"(d[21]), "+f"(d[22]), "+f"(d[23]), "+f"(d[24]), "+f"(d[25]), "+f"(d[26]), "+f"(d[27]), "+f"(d[28]), "+f"(d[29]), "+f"(d[30]), "+f"(d[31]), "+f"(d[32]), "+f"(d[33]), "+f"(d[34]), "+f"(d[35]), "+f"(d[36]), "+f"(d[37]), "+f"(d[38]), "+f"(d[39]), "+f"(d[40]), "+f"(d[41]), "+f"(d[42]), "+f"(d[43]), "+f"(d[44]), "+f"(d[45]), "+f"(d[46]), "+f"(d[47])
        : "r"(a0), "r"(a1), "r"(a2), "r"(a3), "l"(b), "r"(sd), "n"(OFF));
}
template <int OFF> __device__ __forceinline__ void wgmma_rs_k80(float* d, uint32_t a0, uint32_t a1, uint32_t a2, uint32_t a3, uint64_t b, int sd) {
    asm volatile("{ .reg .pred p; .reg .b64 db; setp.ne.b32 p, %45, 0; add.s64 db, %44, %46;\n"
        "wgmma.mma_async.sync.aligned.m64n80k16.f32.bf16.bf16 {%0, %1, %2, %3, %4, %5, %6, %7, %8, %9, %10, %11, %12, %13, %14, %15, %16, %17, %18, %19, %20, %21, %22, %23, %24, %25, %26, %27, %28, %29, %30, %31, %32, %33, %34, %35, %36, %37, %38, %39}, {%40, %41, %42, %43}, db, p, 1, 1, 0; }\n"
        : "+f"(d[0]), "+f"(d[1]), "+f"(d[2]), "+f"(d[3]), "+f"(d[4]), "+f"(d[5]), "+f"(d[6]), "+f"(d[7]), "+f"(d[8]), "+f"(d[9]), "+f"(d[10]), "+f"(d[11]), "+f"(d[12]), "+f"(d[13]), "+f"(d[14]), "+f"(d[15]), "+f"(d[16]), "+f"(d[17]), "+f"(d[18]), "+f"(d[19]), "+f"(d[20]), "+f"(d[21]), "+f"(d[22]), "+f"(d[23]), "+f"(d[24]), "+f"(d[25]), "+f"(d[26]), "+f"(d[27]), "+f"(d[28]), "+f"(d[29]), "+f"(d[30]), "+f"(d[31]), "+f"(d[32]), "+f"(d[33]), "+f"(d[34]), "+f"(d[35]), "+f"(d[36]), "+f"(d[37]), "+f"(d[38]), "+f"(d[39])
        : "r"(a0), "r"(a1), "r"(a2), "r"(a3), "l"(b), "r"(sd), "n"(OFF));
}
template <int OFF> __device__ __forceinline__ void wgmma_rs_k64(float* d, uint32_t a0, uint32_t a1, uint32_t a2, uint32_t a3, uint64_t b, int sd) {
    asm volatile("{ .reg .pred p; .reg .b64 db; setp.ne.b32 p, %37, 0; add.s64 db, %36, %38;\n"
        "wgmma.mma_async.sync.aligned.m64n64k16.f32.bf16.bf16 {%0, %1, %2, %3, %4, %5, %6, %7, %8, %9, %10, %11, %12, %13, %14, %15, %16, %17, %18, %19, %20, %21, %22, %23, %24, %25, %26, %27, %28, %29, %30, %31}, {%32, %33, %34, %35}, db, p, 1, 1, 0; }\n"
        : "+f"(d[0]), "+f"(d[1]), "+f"(d[2]), "+f"(d[3]), "+f"(d[4]), "+f"(d[5]), "+f"(d[6]), "+f"(d[7]), "+f"(d[8]), "+f"(d[9]), "+f"(d[10]), "+f"(d[11]), "+f"(d[12]), "+f"(d[13]), "+f"(d[14]), "+f"(d[15]), "+f"(d[16]), "+f"(d[17]), "+f"(d[18]), "+f"(d[19]), "+f"(d[20]), "+f"(d[21]), "+f"(d[22]), "+f"(d[23]), "+f"(d[24]), "+f"(d[25]), "+f"(d[26]), "+f"(d[27]), "+f"(d[28]), "+f"(d[29]), "+f"(d[30]), "+f"(d[31])
        : "r"(a0), "r"(a1), "r"(a2), "r"(a3), "l"(b), "r"(sd), "n"(OFF));
}
template <int OFF> __device__ __forceinline__ void wgmma_rs_n16(float* d, uint32_t a0, uint32_t a1, uint32_t a2, uint32_t a3, uint64_t b, int sd) {
    asm volatile("{ .reg .pred p; .reg .b64 db; setp.ne.b32 p, %13, 0; add.s64 db, %12, %14;\n"
        "wgmma.mma_async.sync.aligned.m64n16k16.f32.bf16.bf16 {%0, %1, %2, %3, %4, %5, %6, %7}, {%8, %9, %10, %11}, db, p, 1, 1, 1; }\n"
        : "+f"(d[0]), "+f"(d[1]), "+f"(d[2]), "+f"(d[3]), "+f"(d[4]), "+f"(d[5]), "+f"(d[6]), "+f"(d[7])
        : "r"(a0), "r"(a1), "r"(a2), "r"(a3), "l"(b), "r"(sd), "n"(OFF));
}
template <int OFF> __device__ __forceinline__ void wgmma_rs_n32(float* d, uint32_t a0, uint32_t a1, uint32_t a2, uint32_t a3, uint64_t b, int sd) {
    asm volatile("{ .reg .pred p; .reg .b64 db; setp.ne.b32 p, %21, 0; add.s64 db, %20, %22;\n"
        "wgmma.mma_async.sync.aligned.m64n32k16.f32.bf16.bf16 {%0, %1, %2, %3, %4, %5, %6, %7, %8, %9, %10, %11, %12, %13, %14, %15}, {%16, %17, %18, %19}, db, p, 1, 1, 1; }\n"
        : "+f"(d[0]), "+f"(d[1]), "+f"(d[2]), "+f"(d[3]), "+f"(d[4]), "+f"(d[5]), "+f"(d[6]), "+f"(d[7]), "+f"(d[8]), "+f"(d[9]), "+f"(d[10]), "+f"(d[11]), "+f"(d[12]), "+f"(d[13]), "+f"(d[14]), "+f"(d[15])
        : "r"(a0), "r"(a1), "r"(a2), "r"(a3), "l"(b), "r"(sd), "n"(OFF));
}
template <int OFF> __device__ __forceinline__ void wgmma_rs_n64(float* d, uint32_t a0, uint32_t a1, uint32_t a2, uint32_t a3, uint64_t b, int sd) {
    asm volatile("{ .reg .pred p; .reg .b64 db; setp.ne.b32 p, %37, 0; add.s64 db, %36, %38;\n"
        "wgmma.mma_async.sync.aligned.m64n64k16.f32.bf16.bf16 {%0, %1, %2, %3, %4, %5, %6, %7, %8, %9, %10, %11, %12, %13, %14, %15, %16, %17, %18, %19, %20, %21, %22, %23, %24, %25, %26, %27, %28, %29, %30, %31}, {%32, %33, %34, %35}, db, p, 1, 1, 1; }\n"
        : "+f"(d[0]), "+f"(d[1]), "+f"(d[2]), "+f"(d[3]), "+f"(d[4]), "+f"(d[5]), "+f"(d[6]), "+f"(d[7]), "+f"(d[8]), "+f"(d[9]), "+f"(d[10]), "+f"(d[11]), "+f"(d[12]), "+f"(d[13]), "+f"(d[14]), "+f"(d[15]), "+f"(d[16]), "+f"(d[17]), "+f"(d[18]), "+f"(d[19]), "+f"(d[20]), "+f"(d[21]), "+f"(d[22]), "+f"(d[23]), "+f"(d[24]), "+f"(d[25]), "+f"(d[26]), "+f"(d[27]), "+f"(d[28]), "+f"(d[29]), "+f"(d[30]), "+f"(d[31])
        : "r"(a0), "r"(a1), "r"(a2), "r"(a3), "l"(b), "r"(sd), "n"(OFF));
}
template <int OFFA, int OFFB> __device__ __forceinline__ void wgmma_ss_kn128(float* d, uint64_t a, uint64_t b, int sd) {
    asm volatile("{ .reg .pred p; .reg .b64 da, db; setp.ne.b32 p, %66, 0; add.s64 da, %64, %67; add.s64 db, %65, %68;\n"
        "wgmma.mma_async.sync.aligned.m64n128k16.f32.bf16.bf16 {%0, %1, %2, %3, %4, %5, %6, %7, %8, %9, %10, %11, %12, %13, %14, %15, %16, %17, %18, %19, %20, %21, %22, %23, %24, %25, %26, %27, %28, %29, %30, %31, %32, %33, %34, %35, %36, %37, %38, %39, %40, %41, %42, %43, %44, %45, %46, %47, %48, %49, %50, %51, %52, %53, %54, %55, %56, %57, %58, %59, %60, %61, %62, %63}, da, db, p, 1, 1, 0, 1; }\n"
        : "+f"(d[0]), "+f"(d[1]), "+f"(d[2]), "+f"(d[3]), "+f"(d[4]), "+f"(d[5]), "+f"(d[6]), "+f"(d[7]), "+f"(d[8]), "+f"(d[9]), "+f"(d[10]), "+f"(d[11]), "+f"(d[12]), "+f"(d[13]), "+f"(d[14]), "+f"(d[15]), "+f"(d[16]), "+f"(d[17]), "+f"(d[18]), "+f"(d[19]), "+f"(d[20]), "+f"(d[21]), "+f"(d[22]), "+f"(d[23]), "+f"(d[24]), "+f"(d[25]), "+f"(d[26]), "+f"(d[27]), "+f"(d[28]), "+f"(d[29]), "+f"(d[30]), "+f"(d[31]), "+f"(d[32]), "+f"(d[33]), "+f"(d[34]), "+f"(d[35]), "+f"(d[36]), "+f"(d[37]), "+f"(d[38]), "+f"(d[39]), "+f"(d[40]), "+f"(d[41]), "+f"(d[42]), "+f"(d[43]), "+f"(d[44]), "+f"(d[45]), "+f"(d[46]), "+f"(d[47]), "+f"(d[48]), "+f"(d[49]), "+f"(d[50]), "+f"(d[51]), "+f"(d[52]), "+f"(d[53]), "+f"(d[54]), "+f"(d[55]), "+f"(d[56]), "+f"(d[57]), "+f"(d[58]), "+f"(d[59]), "+f"(d[60]), "+f"(d[61]), "+f"(d[62]), "+f"(d[63])
        : "l"(a), "l"(b), "r"(sd), "n"(OFFA), "n"(OFFB));
}
template <int OFFA, int OFFB> __device__ __forceinline__ void wgmma_ss_kn96(float* d, uint64_t a, uint64_t b, int sd) {
    asm volatile("{ .reg .pred p; .reg .b64 da, db; setp.ne.b32 p, %50, 0; add.s64 da, %48, %51; add.s64 db, %49, %52;\n"
        "wgmma.mma_async.sync.aligned.m64n96k16.f32.bf16.bf16 {%0, %1, %2, %3, %4, %5, %6, %7, %8, %9, %10, %11, %12, %13, %14, %15, %16, %17, %18, %19, %20, %21, %22, %23, %24, %25, %26, %27, %28, %29, %30, %31, %32, %33, %34, %35, %36, %37, %38, %39, %40, %41, %42, %43, %44, %45, %46, %47}, da, db, p, 1, 1, 0, 1; }\n"
        : "+f"(d[0]), "+f"(d[1]), "+f"(d[2]), "+f"(d[3]), "+f"(d[4]), "+f"(d[5]), "+f"(d[6]), "+f"(d[7]), "+f"(d[8]), "+f"(d[9]), "+f"(d[10]), "+f"(d[11]), "+f"(d[12]), "+f"(d[13]), "+f"(d[14]), "+f"(d[15]), "+f"(d[16]), "+f"(d[17]), "+f"(d[18]), "+f"(d[19]), "+f"(d[20]), "+f"(d[21]), "+f"(d[22]), "+f"(d[23]), "+f"(d[24]), "+f"(d[25]), "+f"(d[26]), "+f"(d[27]), "+f"(d[28]), "+f"(d[29]), "+f"(d[30]), "+f"(d[31]), "+f"(d[32]), "+f"(d[33]), "+f"(d[34]), "+f"(d[35]), "+f"(d[36]), "+f"(d[37]), "+f"(d[38]), "+f"(d[39]), "+f"(d[40]), "+f"(d[41]), "+f"(d[42]), "+f"(d[43]), "+f"(d[44]), "+f"(d[45]), "+f"(d[46]), "+f"(d[47])
        : "l"(a), "l"(b), "r"(sd), "n"(OFFA), "n"(OFFB));
}
template <int OFFA, int OFFB> __device__ __forceinline__ void wgmma_ss_mn40(float* d, uint64_t a, uint64_t b, int sd) {
    asm volatile("{ .reg .pred p; .reg .b64 da, db; setp.ne.b32 p, %22, 0; add.s64 da, %20, %23; add.s64 db, %21, %24;\n"
        "wgmma.mma_async.sync.aligned.m64n40k16.f32.bf16.bf16 {%0, %1, %2, %3, %4, %5, %6, %7, %8, %9, %10, %11, %12, %13, %14, %15, %16, %17, %18, %19}, da, db, p, 1, 1, 1, 1; }\n"
        : "+f"(d[0]), "+f"(d[1]), "+f"(d[2]), "+f"(d[3]), "+f"(d[4]), "+f"(d[5]), "+f"(d[6]), "+f"(d[7]), "+f"(d[8]), "+f"(d[9]), "+f"(d[10]), "+f"(d[11]), "+f"(d[12]), "+f"(d[13]), "+f"(d[14]), "+f"(d[15]), "+f"(d[16]), "+f"(d[17]), "+f"(d[18]), "+f"(d[19])
        : "l"(a), "l"(b), "r"(sd), "n"(OFFA), "n"(OFFB));
}

constexpr int L_ = 2048, D_ = 512, NS_ = 128, F_ = 1792;
constexpr int BF = 224;
constexpr int NCTA = 128;
constexpr int NTHREADS = 512;
constexpr int NSLOT = 10;
constexpr int SLOT = 16384;
constexpr int TW_OFF = 32;
constexpr int TW_BYTES = (1088 + TW_OFF) * 4;
constexpr int PLANE = 192 * 16;
constexpr int UCH = 2 * PLANE;
constexpr int OFF_U = NSLOT * SLOT;
constexpr int OFF_TW = OFF_U + 2 * UCH;
constexpr int OFF_TE = OFF_TW + 4 * TW_BYTES;
constexpr int OFF_W = OFF_TE + 4096;
constexpr int OFF_STG = OFF_W + 4096;
constexpr int OFF_KST = OFF_TW;
constexpr int KSTAGE = 26624;
constexpr int KC_BYTES = 2608;
constexpr int OFF_VEC = OFF_KST + 2 * KSTAGE;
static_assert(OFF_STG + 26624 <= OFF_VEC, "conv area");
constexpr int OFF_RST = OFF_VEC + BF * 8;
constexpr int OFF_BAR = OFF_RST + 1024;
constexpr int SMEM_BYTES = OFF_BAR + 256;
static_assert(SMEM_BYTES <= 232448, "smem");
constexpr int B_FULL = 0, B_EMPTY = 10, B_U = 20, B_WRDY = 22, B_SFULL = 23, B_PRO = 24, B_WFREE = 25, B_PRO2 = 26, B_TAB = 27, B_VEC = 28, B_PEER = 29, B_CONV = 30, B_SFREE = 31, B_N = 32;

constexpr unsigned long long BAR_COUNTS = 0x318211484311ull;
constexpr int SPIN_LIMIT = 1 << 19;

__device__ uint4 g_xt[D_ * 256];
__device__ __align__(16) float2 g_stats[L_];
__device__ __align__(16) float g_colsum[4 * F_];
__device__ uint4 g_y[D_ * 256 + 16];
constexpr int PART_I = 8 * 3 * 1024 + 8;
__device__ uint4 g_part[16 * PART_I + 8];
__device__ __align__(128) unsigned g_cnt_[16 * 32];
#define g_cnt(i) (g_cnt_ + (i) * 32)

struct Params {
    const __nv_bfloat16 *x, *Are, *Aim, *Bre, *Bim, *Cre, *Cim, *logdt, *dskip, *w1, *b1, *w2, *b2;
};

__device__ __forceinline__ uint32_t smem_u32(const void* p) { return (uint32_t)__cvta_generic_to_shared(p); }
__device__ __forceinline__ void mbar_init(uint32_t bar, int cnt) { asm volatile("mbarrier.init.shared::cta.b64 [%0], %1;" ::"r"(bar), "r"(cnt)); }
__device__ __forceinline__ void mbar_expect_tx(uint32_t bar, uint32_t bytes) { asm volatile("mbarrier.arrive.expect_tx.shared::cta.b64 _, [%0], %1;" ::"r"(bar), "r"(bytes) : "memory"); }
__device__ __forceinline__ void mbar_arrive(uint32_t bar) { asm volatile("mbarrier.arrive.shared::cta.b64 _, [%0];" ::"r"(bar) : "memory"); }
__device__ __forceinline__ bool mbar_try(uint32_t bar, uint32_t parity) {
    uint32_t ok;
    asm volatile("{ .reg .pred p; mbarrier.try_wait.parity.shared::cta.b64 p, [%1], %2; selp.u32 %0, 1, 0, p; }" : "=r"(ok) : "r"(bar), "r"(parity) : "memory");
    return ok;
}
__device__ __forceinline__ void mbar_wait(uint32_t bar, uint32_t parity) {
    asm volatile("{ .reg .pred p; .reg .u32 n; mov.u32 n, 0;\n"
                 "W: mbarrier.try_wait.parity.shared::cta.b64 p, [%0], %1;\n"
                 "@p bra.uni D;\n"
                 "add.u32 n, n, 1; setp.lt.u32 p, n, %2;\n"
                 "@p bra.uni W;\n"
                 "D: }" ::"r"(bar), "r"(parity), "n"(SPIN_LIMIT) : "memory");
}
__device__ __forceinline__ uint32_t map_peer(uint32_t addr) {
    uint32_t r;
    asm volatile("mapa.shared::cluster.u32 %0, %1, %2;" : "=r"(r) : "r"(addr), "r"((blockIdx.x & 1) ^ 1));
    return r;
}
__device__ __forceinline__ unsigned ld_acquire(const unsigned* p) { unsigned v; asm volatile("ld.acquire.gpu.global.u32 %0, [%1];" : "=r"(v) : "l"(p) : "memory"); return v; }
__device__ __forceinline__ unsigned ld_relaxed(const unsigned* p) { unsigned v; asm volatile("ld.relaxed.gpu.global.u32 %0, [%1];" : "=r"(v) : "l"(p) : "memory"); return v; }
__device__ __forceinline__ void wait_flag(const unsigned* p, unsigned target) {
#pragma unroll 1
    for (int it = 0; it < SPIN_LIMIT; it++) { if ((int)(ld_acquire(p) - target) >= 0) break; __nanosleep(32); }
}
__device__ __forceinline__ uint4 ld_relaxed128(const uint4* p) {
    uint4 v;
    asm volatile("ld.relaxed.gpu.global.v4.u32 {%0, %1, %2, %3}, [%4];" : "=r"(v.x), "=r"(v.y), "=r"(v.z), "=r"(v.w) : "l"(p) : "memory");
    return v;
}
__device__ __forceinline__ void st_relaxed128(uint4* p, uint32_t x, uint32_t y, uint32_t z, uint32_t w) {
    asm volatile("st.relaxed.gpu.global.v4.u32 [%0], {%1, %2, %3, %4};" ::"l"(p), "r"(x), "r"(y), "r"(z), "r"(w) : "memory");
}
__device__ __forceinline__ float rcp_fast(float x) { float r; asm("rcp.approx.ftz.f32 %0, %1;" : "=f"(r) : "f"(x)); return r; }
__device__ __forceinline__ float sqrt_fast(float x) { float r; asm("sqrt.approx.ftz.f32 %0, %1;" : "=f"(r) : "f"(x)); return r; }
__device__ __forceinline__ uint4 ldg128(const void* p) {
    uint4 v;
    asm volatile("ld.global.nc.v4.u32 {%0, %1, %2, %3}, [%4];" : "=r"(v.x), "=r"(v.y), "=r"(v.z), "=r"(v.w) : "l"(p));
    return v;
}
__device__ __forceinline__ uint4 ldv128(const void* p) {
    uint4 v;
    asm volatile("ld.global.v4.u32 {%0, %1, %2, %3}, [%4];" : "=r"(v.x), "=r"(v.y), "=r"(v.z), "=r"(v.w) : "l"(p) : "memory");
    return v;
}
__device__ __forceinline__ uint2 ldv64(const void* p) { uint2 v; asm volatile("ld.global.v2.u32 {%0, %1}, [%2];" : "=r"(v.x), "=r"(v.y) : "l"(p) : "memory"); return v; }
__device__ __forceinline__ uint32_t ldv32(const void* p) { uint32_t v; asm volatile("ld.global.u32 %0, [%1];" : "=r"(v) : "l"(p) : "memory"); return v; }
__device__ __forceinline__ uint32_t ldv16(const void* p) { uint16_t v; asm volatile("ld.global.u16 %0, [%1];" : "=h"(v) : "l"(p) : "memory"); return v; }
__device__ __forceinline__ uint2 ldg64(const void* p) { uint2 v; asm volatile("ld.global.nc.v2.u32 {%0, %1}, [%2];" : "=r"(v.x), "=r"(v.y) : "l"(p)); return v; }
__device__ __forceinline__ uint32_t ldg32(const void* p) { uint32_t v; asm volatile("ld.global.nc.u32 %0, [%1];" : "=r"(v) : "l"(p)); return v; }
__device__ __forceinline__ uint32_t ldg16(const void* p) { uint16_t v; asm volatile("ld.global.nc.u16 %0, [%1];" : "=h"(v) : "l"(p)); return v; }
__device__ __forceinline__ void fence_gpu() { asm volatile("fence.acq_rel.gpu;" ::: "memory"); }
__device__ __forceinline__ void fence_async_smem() { asm volatile("fence.proxy.async.shared::cta;" ::: "memory"); }
template <int ID, int N> __device__ __forceinline__ void bar_sync() { asm volatile("bar.sync %0, %1;" ::"n"(ID), "n"(N) : "memory"); }
__device__ __forceinline__ void sched_fence() { asm volatile("{ .reg .pred p; setp.eq.u32 p, %0, 0x7fffffff; @p exit; }" ::"r"(blockIdx.x) : "memory"); }
__device__ __forceinline__ void wg_fence() { asm volatile("wgmma.fence.sync.aligned;" ::: "memory"); }
__device__ __forceinline__ void wg_commit() { asm volatile("wgmma.commit_group.sync.aligned;" ::: "memory"); }
template <int N> __device__ __forceinline__ void wg_wait() { asm volatile("wgmma.wait_group.sync.aligned %0;" ::"n"(N) : "memory"); }
__device__ __forceinline__ uint32_t lds32(uint32_t a) { uint32_t v; asm volatile("ld.shared.u32 %0, [%1];" : "=r"(v) : "r"(a) : "memory"); return v; }
__device__ __forceinline__ float2 lds64f(uint32_t a) { float2 v; asm volatile("ld.shared.v2.f32 {%0, %1}, [%2];" : "=f"(v.x), "=f"(v.y) : "r"(a) : "memory"); return v; }
__device__ __forceinline__ uint2 lds64(uint32_t a) { uint2 v; asm volatile("ld.shared.v2.u32 {%0, %1}, [%2];" : "=r"(v.x), "=r"(v.y) : "r"(a) : "memory"); return v; }
__device__ __forceinline__ uint4 lds128(uint32_t a) { uint4 v; asm volatile("ld.shared.v4.u32 {%0, %1, %2, %3}, [%4];" : "=r"(v.x), "=r"(v.y), "=r"(v.z), "=r"(v.w) : "r"(a) : "memory"); return v; }
__device__ __forceinline__ float4 lds128f(uint32_t a) { float4 v; asm volatile("ld.shared.v4.f32 {%0, %1, %2, %3}, [%4];" : "=f"(v.x), "=f"(v.y), "=f"(v.z), "=f"(v.w) : "r"(a) : "memory"); return v; }
__device__ __forceinline__ void sts32(uint32_t a, uint32_t v) { asm volatile("st.shared.u32 [%0], %1;" ::"r"(a), "r"(v) : "memory"); }
__device__ __forceinline__ void sts64f(uint32_t a, float x, float y) { asm volatile("st.shared.v2.f32 [%0], {%1, %2};" ::"r"(a), "f"(x), "f"(y) : "memory"); }
__device__ __forceinline__ void sts128(uint32_t a, uint32_t x, uint32_t y, uint32_t z, uint32_t w) { asm volatile("st.shared.v4.u32 [%0], {%1, %2, %3, %4};" ::"r"(a), "r"(x), "r"(y), "r"(z), "r"(w) : "memory"); }
__device__ __forceinline__ void sts128f(uint32_t a, float x, float y, float z, float w) { asm volatile("st.shared.v4.f32 [%0], {%1, %2, %3, %4};" ::"r"(a), "f"(x), "f"(y), "f"(z), "f"(w) : "memory"); }
__device__ __forceinline__ uint32_t pack_bf16(float lo, float hi) { uint32_t r; asm("cvt.rn.bf16x2.f32 %0, %1, %2;" : "=r"(r) : "f"(hi), "f"(lo)); return r; }
__device__ __forceinline__ float bf_lo(uint32_t v) { return __uint_as_float(v << 16); }
__device__ __forceinline__ float bf_hi(uint32_t v) { return __uint_as_float(v & 0xffff0000u); }
__device__ __forceinline__ float bf_round(float x) { return bf_hi(pack_bf16(0.f, x)); }
__device__ __forceinline__ float bf_ld(const __nv_bfloat16* p) { return __bfloat162float(__ldg(p)); }
__device__ __forceinline__ float ex2f(float x) { float r; asm("ex2.approx.ftz.f32 %0, %1;" : "=f"(r) : "f"(x)); return r; }
__device__ __forceinline__ float tanh_fast(float x) { float r; asm("tanh.approx.f32 %0, %1;" : "=f"(r) : "f"(x)); return r; }
__device__ __forceinline__ float warp_sum(float v) {
#pragma unroll
    for (int o = 16; o > 0; o >>= 1) v += __shfl_xor_sync(0xffffffffu, v, o);
    return v;
}
__device__ __forceinline__ void tma_load_3d(uint32_t dst, const CUtensorMap* tm, uint32_t bar, int c0, int c1, int c2) {
    asm volatile("cp.async.bulk.tensor.3d.shared::cluster.global.mbarrier::complete_tx::bytes [%0], [%1, {%3, %4, %5}], [%2];" ::"r"(dst), "l"(tm), "r"(bar), "r"(c0), "r"(c1), "r"(c2) : "memory");
}
__device__ __forceinline__ void bulk_load(uint32_t dst, const void* src, uint32_t bytes, uint32_t bar) {
    asm volatile("cp.async.bulk.shared::cluster.global.mbarrier::complete_tx::bytes [%0], [%1], %2, [%3];" ::"r"(dst), "l"(src), "r"(bytes), "r"(bar) : "memory");
}
__device__ __forceinline__ void bulk_store(void* dst, uint32_t src, uint32_t bytes) {
    asm volatile("cp.async.bulk.global.shared::cta.bulk_group [%0], [%1], %2;" ::"l"(dst), "r"(src), "r"(bytes) : "memory");
}
__device__ __forceinline__ void stg128(void* p, uint32_t x, uint32_t y, uint32_t z, uint32_t w) { asm volatile("st.global.v4.u32 [%0], {%1, %2, %3, %4};" ::"l"(p), "r"(x), "r"(y), "r"(z), "r"(w) : "memory"); }
__device__ __forceinline__ void stg64f(void* p, float x, float y) { asm volatile("st.global.v2.f32 [%0], {%1, %2};" ::"l"(p), "f"(x), "f"(y) : "memory"); }
__device__ __forceinline__ void sts64(uint32_t a, uint32_t x, uint32_t y) { asm volatile("st.shared.v2.u32 [%0], {%1, %2};" ::"r"(a), "r"(x), "r"(y) : "memory"); }
__host__ __device__ constexpr uint64_t make_desc(uint32_t addr, uint32_t lbo, uint32_t sbo, uint32_t swz) {
    return (uint64_t)(((addr & 0x3FFFF) >> 4) | ((lbo >> 4) << 16)) | ((uint64_t)((sbo >> 4) | (swz << 30)) << 32);
}
__device__ __forceinline__ void ldsm_x4(uint32_t a, uint32_t* r) {
    asm volatile("ldmatrix.sync.aligned.m8n8.x4.shared.b16 {%0, %1, %2, %3}, [%4];" : "=r"(r[0]), "=r"(r[1]), "=r"(r[2]), "=r"(r[3]) : "r"(a) : "memory");
}
__device__ __forceinline__ void ldsm_x4_t(uint32_t a, uint32_t* r) {
    asm volatile("ldmatrix.sync.aligned.m8n8.x4.trans.shared.b16 {%0, %1, %2, %3}, [%4];" : "=r"(r[0]), "=r"(r[1]), "=r"(r[2]), "=r"(r[3]) : "r"(a) : "memory");
}
__device__ __forceinline__ void stsm_x4(uint32_t a, uint32_t r0, uint32_t r1, uint32_t r2, uint32_t r3) {
    asm volatile("stmatrix.sync.aligned.m8n8.x4.shared.b16 [%0], {%1, %2, %3, %4};" ::"r"(a), "r"(r0), "r"(r1), "r"(r2), "r"(r3) : "memory");
}
__device__ __forceinline__ void stsm_x4_t(uint32_t a, uint32_t r0, uint32_t r1, uint32_t r2, uint32_t r3) {
    asm volatile("stmatrix.sync.aligned.m8n8.x4.trans.shared.b16 [%0], {%1, %2, %3, %4};" ::"r"(a), "r"(r0), "r"(r1), "r"(r2), "r"(r3) : "memory");
}
struct cplx { float r, i; };
__device__ __forceinline__ cplx cmul(cplx a, cplx b) { return {fmaf(a.r, b.r, -a.i * b.i), fmaf(a.r, b.i, a.i * b.r)}; }
__device__ __forceinline__ cplx cmul_conj(cplx a, cplx b) { return {fmaf(a.r, b.r, -a.i * b.i), fmaf(-a.r, b.i, -a.i * b.r)}; }
__device__ __forceinline__ cplx csq(cplx a) { return {fmaf(a.r, a.r, -a.i * a.i), (a.r + a.r) * a.i}; }
__device__ __forceinline__ float rint_small(float x) { return __fadd_rn(__fadd_rn(x, 12582912.f), -12582912.f); }
__device__ __forceinline__ cplx zpow(float a2, float rev, float e) {
    float m = ex2f(a2 * e);
    float f = rev * e;
    f -= rint_small(f);
    float th = f * 6.283185307179586f;
    return {m * __cosf(th), m * __sinf(th)};
}

#define STAMP(k) do { } while (0)
#define REG_MLP 168
#define REG_CONV 128
#define REG_AUX 48
#define VSTAMP(k) do { } while (0)
#define KSTAMP(k) do { } while (0)
#define CSTAMP(k) do { } while (0)
#define GSTAMP(k) STAMP(k)
#define GELU_SERIAL 0
#define GATHER_LATE 1
#define TMA_DELAY 1000
#define CONV_PAUSE 0
#define YIELD_STEP 8
#define YIELD_AT 5
#define KGEN2 2
#define PINGPONG 3
#define VCH 2
#define SMALL_FROM 8
#define GATE_LATE 0
#define A3_LDS 1
#define GATE_KB 0
#define CONV_NBUF 3
#define CONV_BATCH 2
#define CONV_GRAN 16

__device__ __forceinline__ uint32_t add2(uint32_t a, uint32_t b) { uint32_t r; asm("add.rn.bf16x2 %0, %1, %2;" : "=r"(r) : "r"(a), "r"(b)); return r; }
__device__ __forceinline__ uint32_t fma2(uint32_t a, uint32_t b, uint32_t c) { uint32_t r; asm("fma.rn.bf16x2 %0, %1, %2, %3;" : "=r"(r) : "r"(a), "r"(b), "r"(c)); return r; }
__device__ __forceinline__ uint32_t mul2(uint32_t a, uint32_t b) { uint32_t r; asm("mul.rn.bf16x2 %0, %1, %2;" : "=r"(r) : "r"(a), "r"(b)); return r; }
__device__ __forceinline__ float bf_hi_fast(uint32_t v) { return __uint_as_float(v); }
template <int LUT> __device__ __forceinline__ uint32_t lop3(uint32_t a, uint32_t b, uint32_t c) {
    uint32_t r;
    asm("lop3.b32 %0, %1, %2, %3, %4;" : "=r"(r) : "r"(a), "r"(b), "r"(c), "n"(LUT));
    return r;
}
__device__ __forceinline__ uint32_t fresh_tid() { uint32_t t; asm volatile("mov.u32 %0, %%tid.x;" : "=r"(t)); return t; }
template <int V> struct IC { __host__ __device__ constexpr operator int() const { return V; } };
template <int N, int I = 0, typename F> __device__ __forceinline__ void static_for(F&& f) {
    if constexpr (I < N) { f(IC<I>{}); static_for<N, I + 1>(f); }
}
__device__ __forceinline__ int tile_i() { return ((blockIdx.x >> 1) & 7) | ((blockIdx.x >> 6) << 3); }
__device__ __forceinline__ int tile_j() { return (blockIdx.x & 1) | (((blockIdx.x >> 4) & 3) << 1); }
__device__ __forceinline__ int block_of_step(int tj, int s) { return ((((tj >> 1) + (0x0E79 >> (2 * s))) & 3) << 1) | ((tj ^ (0x47 >> s)) & 1); }

struct ConvCtx { uint32_t tw, te, zero, wbar, wpar, last, dbg; uint64_t du, dw; };
constexpr int FAR0 = 6;
__host__ __device__ constexpr int conv_item(int i) { return i < FAR0 ? i : i < FAR0 + 8 ? 17 + i - FAR0 : i - 8; }
template <int I> __device__ __forceinline__ void conv_load_one(uint32_t* a, const ConvCtx& c) {
    const uint32_t ad = I < 17 ? c.tw + I * 256 : c.te + ((I - 17) >> 2) * 512 - ((I - 17) & 3) * 64;
    a[0] = lds32(ad); a[1] = lds32(ad + 32); a[2] = lds32(ad - 32);
    a[3] = lds32(ad);
}
template <int I> __device__ __forceinline__ void conv_issue_one(float* d, float* d3, const uint32_t* a, const ConvCtx& c) {
    constexpr int N = I >= 17 ? 0 : CONV_GRAN == 16 ? 128 - 16 * (I / 4) : I < 8 ? 128 : 96;
    if constexpr (N == 128) wgmma_rs_k128<4 * I>(d, a[0], a[1], a[2], a[3], c.du, I != 0);
    else if constexpr (N == 112) wgmma_rs_k112<4 * I>(d, a[0], a[1], a[2], a[3], c.du, 1);
    else if constexpr (N == 96) wgmma_rs_k96<4 * I>(d, a[0], a[1], a[2], a[3], c.du, 1);
    else if constexpr (N == 80) wgmma_rs_k80<4 * I>(d, a[0], a[1], a[2], a[3], c.du, 1);
    else if constexpr (N == 64) wgmma_rs_k64<4 * I>(d, a[0], a[1], a[2], a[3], c.du, 1);
    else wgmma_rs_n16<((I - 17) >> 2) * 128 + ((I - 17) & 3) * 16>(d3, a[0], a[1], a[2], a[3], c.dw, I != 17);
}
constexpr int CB = CONV_BATCH, NCB = (25 + CB - 1) / CB;
template <int B> __device__ __forceinline__ void conv_load(uint32_t (*a)[4], const ConvCtx& c) {
    static_for<CB>([&](auto i) { if constexpr (CB * B + i < 25) conv_load_one<conv_item(CB * B + i)>(a[i], c); });
}
constexpr int NBUF = CONV_NBUF;
template <int B> struct ConvBatches {
    static __device__ __forceinline__ void run(float* d, float* d3, uint32_t (*a)[CB][4], const ConvCtx& c) {
        if constexpr (B == FAR0 / CB) { if (threadIdx.x == 256 && c.dbg) VSTAMP(23); mbar_wait(c.wbar, c.wpar); if (threadIdx.x == 256 && c.dbg) VSTAMP(24); }
        if constexpr (B == YIELD_AT && YIELD_STEP < 8) { if (c.last) asm volatile("bar.arrive 10, 384;" ::: "memory"); }
        wg_fence();
        static_for<CB>([&](auto i) { if constexpr (CB * B + i < 25) conv_issue_one<conv_item(CB * B + i)>(d, d3, a[B % NBUF][i], c); });
        wg_commit();
        if constexpr (B + NBUF - 1 < NCB) {
            if constexpr (B > 0) wg_wait<1>();
            if constexpr (B == (FAR0 + 7) / CB + 1) { __syncwarp(); if ((threadIdx.x & 31) == 0) mbar_arrive(c.wbar + (B_WFREE - B_WRDY) * 8); }
            conv_load<B + NBUF - 1>(a[(B + NBUF - 1) % NBUF], c);
        }
        if constexpr (B + 1 < NCB) ConvBatches<B + 1>::run(d, d3, a, c);
    }
};
__device__ __forceinline__ void conv_windows(uint32_t ua, uint32_t wa, int hl) {
    const uint2 v0 = lds64(ua + PLANE + 16 + 8), v3 = lds64(ua - 16);
    const uint4 v1 = lds128(ua), v2 = lds128(ua + PLANE);
    const uint32_t pk[12] = {v0.x, v0.y, v1.x, v1.y, v1.z, v1.w, v2.x, v2.y, v2.z, v2.w, v3.x, v3.y};
#pragma unroll
    for (int hf = 0; hf < 2; hf++) {
        float u[16], w7[8];
#pragma unroll
        for (int i = 0; i < 8; i++) { u[2 * i] = bf_lo(pk[4 * hf + i]); u[2 * i + 1] = bf_hi(pk[4 * hf + i]); }
        const float b6 = u[6] + u[7], m0 = (u[4] + u[5]) + b6, c9 = u[8] + u[9], m1 = c9 + (u[10] + u[11]);
        const float a2 = u[2] + u[3], d13 = u[12] + u[13];
        w7[0] = (u[1] + a2) + m0; w7[1] = (a2 + m0) + u[8]; w7[2] = (u[3] + m0) + c9; w7[3] = m0 + (c9 + u[10]);
        w7[4] = (u[5] + b6) + m1; w7[5] = (b6 + m1) + u[12]; w7[6] = (u[7] + m1) + d13; w7[7] = m1 + (d13 + u[14]);
        uint32_t o[4];
#pragma unroll
        for (int i = 0; i < 4; i++) o[i] = pack_bf16(w7[2 * i] + (u[2 * i] + u[2 * i + 8]), w7[2 * i + 1] + (u[2 * i + 1] + u[2 * i + 9]));
        if (hl < 64) sts128(wa + hf * 1024, o[0], o[1], o[2], o[3]);
        if (hf ? hl < 64 : hl > 0) sts128(wa + 2048 + (hf ? 0 : 1024 - 16), pack_bf16(w7[0], w7[1]), pack_bf16(w7[2], w7[3]), pack_bf16(w7[4], w7[5]), pack_bf16(w7[6], w7[7]));
    }
}
__device__ __forceinline__ void colsum_slice(uint32_t sb, int half, int lane, uint32_t bars, float* dst) {
    float cs[8] = {0.f, 0.f, 0.f, 0.f, 0.f, 0.f, 0.f, 0.f};
    const int l28 = lane < 28 ? lane : 0, rg = l28 / 7;
    const uint32_t base = sb + (NSLOT - 2) * SLOT, src = base + half * 7168 + rg * 112 + (l28 - 7 * rg) * 16;
    mbar_wait(bars + B_VEC * 8, 0);
#pragma unroll 4
    for (int r = 0; r < 16; r++) {
        const uint4 v = lds128(src + r * 448);
        cs[0] += bf_lo(v.x); cs[1] += bf_hi(v.x); cs[2] += bf_lo(v.y); cs[3] += bf_hi(v.y);
        cs[4] += bf_lo(v.z); cs[5] += bf_hi(v.z); cs[6] += bf_lo(v.w); cs[7] += bf_hi(v.w);
    }
#pragma unroll
    for (int k = 0; k < 8; k++) { cs[k] += __shfl_down_sync(0xffffffffu, cs[k], 14); cs[k] += __shfl_down_sync(0xffffffffu, cs[k], 7); }
    if (half && lane < 7) {
        sts128f(base + 7168 + lane * 32, cs[0], cs[1], cs[2], cs[3]);
        sts128f(base + 7168 + lane * 32 + 16, cs[4], cs[5], cs[6], cs[7]);
    }
    bar_sync<0, 64>();
    if (!half) {
        if (lane < 7) {
            const float4 o0 = lds128f(base + 7168 + lane * 32), o1 = lds128f(base + 7168 + lane * 32 + 16);
            sts128f(base + lane * 32, cs[0] + o0.x, cs[1] + o0.y, cs[2] + o0.z, cs[3] + o0.w);
            sts128f(base + lane * 32 + 16, cs[4] + o1.x, cs[5] + o1.y, cs[6] + o1.z, cs[7] + o1.w);
        }
        fence_async_smem();
        __syncwarp();
        if (lane == 0) {
            bulk_store(dst, bars - OFF_BAR + (NSLOT - 2) * SLOT, 224);
            asm volatile("cp.async.bulk.commit_group;" ::: "memory");
            asm volatile("cp.async.bulk.wait_group 0;" ::: "memory");
            asm volatile("red.global.add.u32 [%0], 1;" ::"l"(g_cnt(2)) : "memory");
            asm volatile("mbarrier.arrive.shared::cta.b64 _, [%0], 8;" ::"r"(bars + (B_EMPTY + NSLOT - 2) * 8) : "memory");
        }
    }
}

__global__ void __cluster_dims__(2, 1, 1) __launch_bounds__(NTHREADS, 1)
fused_kernel(const Params p, const __grid_constant__ CUtensorMap tmX, const __grid_constant__ CUtensorMap tmW1,
             const __grid_constant__ CUtensorMap tmW2, const __grid_constant__ CUtensorMap tmO, const __grid_constant__ CUtensorMap tmT,
             const __grid_constant__ CUtensorMap tmC, const __grid_constant__ CUtensorMap tmY) {
    extern __shared__ __align__(1024) unsigned char smem_raw[];
    const uint32_t sc = smem_u32(smem_raw);
    const uint32_t sb = sc;
    constexpr uint32_t sd = 1024;
    const uint32_t bars = sc + OFF_BAR;
    const uint32_t epoch_addr = sb + OFF_RST + 128;
    if (threadIdx.x == 0) STAMP(31);
    uint32_t er[32];
    if (threadIdx.x < 256) {
        const int bi = tile_i(), bj = tile_j();
        const char* xb = (const char*)p.x + (unsigned)(((bi * 8 + (bj >> 1) * 2) * 16 + (bj & 1) * 8) * (D_ * 2));
        const char* s0 = xb + (threadIdx.x >> 5) * (D_ * 2) + (threadIdx.x & 31) * 16;
        const char* s1 = xb + ((threadIdx.x & 1) ? 0 : 16 * D_ * 2) + (threadIdx.x >> 1) * 8;
#pragma unroll
        for (int k = 0; k < 4; k++) {
            const uint4 v = ldv128(s0 + (k < 2 ? 16 * D_ * 2 : 0) + (k & 1) * 512);
            er[4 * k] = v.x; er[4 * k + 1] = v.y; er[4 * k + 2] = v.z; er[4 * k + 3] = v.w;
        }
#pragma unroll
        for (int r = 0; r < 8; r++) { const uint2 v = ldv64(s1 + r * (D_ * 2)); er[16 + 2 * r] = v.x; er[17 + 2 * r] = v.y; }
    } else if (threadIdx.x < 384) {
        const unsigned d = blockIdx.x * 4 + ((threadIdx.x >> 6) & 1), o = d * (NS_ * 2) + (threadIdx.x & 63) * 4;
#pragma unroll
        for (int pr = 0; pr < 2; pr++) {
            er[pr * 8] = ldv32((const char*)p.Are + o + pr * 512); er[pr * 8 + 1] = ldv32((const char*)p.Aim + o + pr * 512);
            er[pr * 8 + 2] = ldv32((const char*)p.Bre + o + pr * 512); er[pr * 8 + 3] = ldv32((const char*)p.Bim + o + pr * 512);
            er[pr * 8 + 4] = ldv32((const char*)p.Cre + o + pr * 512); er[pr * 8 + 5] = ldv32((const char*)p.Cim + o + pr * 512);
            er[pr * 8 + 6] = ldv16(p.logdt + d + pr * 2);
        }
        er[7] = ldv16(p.dskip + blockIdx.x * 4 + ((threadIdx.x >> 5) & 3));
        er[15] = ldv16(p.b2 + blockIdx.x * 4 + (threadIdx.x & 3));
    }
    if ((threadIdx.x >> 5) == 12) {
        if (threadIdx.x == 384) {
#pragma unroll
            for (int i = 0; i < B_N; i++) mbar_init(bars + i * 8, i < B_U ? (i < B_EMPTY ? 1 : 8) : (int)((BAR_COUNTS >> (4 * (i - B_U))) & 15));
            asm volatile("fence.mbarrier_init.release.cluster;" ::: "memory");
            if ((sc & 0x3ffffu) != sd) __trap();
            STAMP(28);
        }
        __syncwarp();
        asm volatile("bar.arrive 7, 128;" ::: "memory");
    }
    const int role = __shfl_sync(0xffffffffu, (int)threadIdx.x >> 7, 0);

    if (role == 3) {
        asm volatile("setmaxnreg.dec.sync.aligned.u32 %0;" ::"n"(REG_AUX));
        const int lane = threadIdx.x & 31, warp = __shfl_sync(0xffffffffu, (int)threadIdx.x >> 5, 0);
        const int ti = tile_i(), tj = tile_j();
        if (warp == 12) {
            if (lane == 0) {
                { const unsigned c0 = clock(); while ((unsigned)clock() - c0 < TMA_DELAY) { } }
                uint32_t em = 0xff;
                int slot = 0;
                auto acquire = [&](uint32_t bytes) {
                    mbar_wait(bars + (B_EMPTY + slot) * 8, (em >> slot) & 1);
                    em ^= 1u << slot;
                    mbar_expect_tx(bars + (B_FULL + slot) * 8, bytes);
                };
#pragma unroll 1
                for (int kb = 0; kb < 8; kb++) {
                    acquire(16384);
                    tma_load_3d(sc + slot * SLOT, &tmX, bars + (B_FULL + slot) * 8, kb * 64, ti * 128, 0);
                    if (++slot == NSLOT) slot = 0;
#pragma unroll 1
                    for (int hf = 0; hf < 2; hf++) {
                        acquire(16384);
                        tma_load_3d(sc + slot * SLOT, &tmW1, bars + (B_FULL + slot) * 8, hf * 128, tj, kb * 64);
                        tma_load_3d(sc + slot * SLOT + 8192, &tmW1, bars + (B_FULL + slot) * 8, hf * 128 + 64, tj, kb * 64);
                        if (++slot == NSLOT) slot = 0;
                    }
                    if (kb == 0) {
                        mbar_arrive(bars + B_VEC * 8);
                        mbar_expect_tx(bars + B_VEC * 8, 128 * 112);
                        tma_load_3d(sc + (NSLOT - 2) * SLOT, &tmC, bars + B_VEC * 8, tj * BF + (ti >> 2) * 56, (ti & 3) * 128, 0);
                    }
                }
                slot = 4;
#pragma unroll 1
                for (int s = 0; s < 16; s++) {
                    acquire(112 * 128);
                    tma_load_3d(sc + slot * SLOT, &tmW2, bars + (B_FULL + slot) * 8, block_of_step(tj, s >> 1) * 64, tj * BF + (s & 1) * 112, 0);
                    if (++slot == 6) slot = 0;
                    if (s == 13) {
                        mbar_expect_tx(bars + (B_FULL + 6) * 8, 16384);
                        tma_load_3d(sc + 6 * SLOT, &tmX, bars + (B_FULL + 6) * 8, tj * 64, ti * 128, 0);
                    }
                }
            }
        } else {
            const uint32_t stg = sb + OFF_STG;
            auto load_u = [&](int k0, int k1) {
#pragma unroll 1
                for (int k = k0; k < k1; k++) {
                    const uint32_t bar = bars + (B_U + ((k >> 1) & 1)) * 8;
                    if (!(k & 1)) mbar_expect_tx(bar, 4096);
                    bulk_load(sc + OFF_U + (k & 3) * PLANE, g_xt + (size_t)(blockIdx.x * 8 + k) * 128, 2048, bar);
                }
            };
            if (warp == 13) {
                unsigned epoch = 0;
                if (lane < 7) asm volatile("prefetch.tensormap [%0];" ::"l"((const char*)&tmX + lane * 128) : "memory");
                if (lane == 0) asm volatile("atom.global.add.u32 %0, [%1], 1;" : "=r"(epoch) : "l"(g_cnt(0)) : "memory");
                bar_sync<7, 128>();
                if (lane == 0) {
                    epoch >>= 7;
                    sts32(epoch_addr, epoch);
                    const int blk = ti * 8 + (tj >> 1) * 2;
                    mbar_wait(bars + B_PRO * 8, 0);
                    asm volatile("cp.async.bulk.tensor.3d.global.shared::cta.bulk_group [%0, {%2, %3, %4}], [%1];" ::"l"(&tmT), "r"(sc + (NSLOT - 1) * SLOT),
                                 "r"(((tj & 1) * 128 + 126 - blk) * 8), "r"(0), "r"(0) : "memory");
                    bulk_store(g_stats + (ti * 8 + tj) * 16, sc + OFF_RST + 256, 128);
                    asm volatile("cp.async.bulk.commit_group;" ::: "memory");
                    asm volatile("cp.async.bulk.wait_group 0;" ::: "memory");
                    asm volatile("red.global.add.u32 [%0], 1;" ::"l"(g_cnt(1)) : "memory");
                    asm volatile("mbarrier.arrive.shared::cta.b64 _, [%0], 8;" ::"r"(bars + (B_EMPTY + NSLOT - 1) * 8) : "memory");
                    STAMP(17);
                    wait_flag(g_cnt(1), (epoch + 1u) * NCTA);
                    STAMP(20);
                    load_u(0, 4);
                    mbar_arrive(bars + B_PRO2 * 8);
                    asm volatile("cp.async.bulk.prefetch.L2.global [%0], %1;" ::"l"((const char*)p.w2 + blockIdx.x * 14336), "r"(14336) : "memory");
                }
            } else {
                const int hf = warp - 14;
                if (hf == 0) {
#pragma unroll
                    for (int k = 0; k < 8; k++) sts128(sb + OFF_U + (k >> 1) * PLANE + 2048 + ((k & 1) * 32 + lane) * 16, 0u, 0u, 0u, 0u);
                    bar_sync<7, 128>();
                    asm volatile("bar.arrive 5, 288;" ::: "memory");
                    fence_async_smem();
                } else {
                    bar_sync<7, 128>();
                    asm volatile("bar.arrive 6, 160;" ::: "memory");
                }
                colsum_slice(sb, hf, lane, bars, g_colsum + (ti & 3) * F_ + tj * BF + (ti >> 2) * 56);
            }
            __syncwarp();
            const int hl = threadIdx.x - 416;
#pragma unroll 1
            for (int c = -1; c < 4; c++) {
                const int hl = fresh_tid() - 416;
                if (c >= 0) mbar_wait(bars + B_SFULL * 8, c & 1);
                if (hl == 0 && (c == 0 || c == 1)) load_u(2 * c + 4, 2 * c + 6);
                __syncwarp();
                if (c < 0) mbar_wait(bars + B_TAB * 8, 0);
                if (c >= 0) {
                    const uint32_t b2 = lds32(stg + 26624 + c * 4);
                    if (c == 2) { if (hl == 0) asm volatile("cp.async.bulk.wait_group.read 0;" ::: "memory"); bar_sync<3, 96>(); }
                    uint4 v[5];
                    auto fetch = [&](uint32_t k16) {
                        const uint32_t sa = stg + k16;
#pragma unroll
                        for (int ww = 0; ww < 4; ww++) v[ww] = lds128(sa + ww * 4096);
                        v[4] = lds128((k16 & 1024) ? sb + OFF_U + 2048 : sa + 16384 - ((k16 >> 1) & 1024));
                    };
                    const int nit = c == 3 ? (warp == 13 ? 2 : 1) : warp == 15 ? 2 : 3;
                    const uint32_t kstep = c == 3 ? 3584 : 1536;
#pragma unroll 1
                    for (int it = 0; it < nit; it++) {
                        const uint32_t k16 = hl * 16 + it * kstep;
                        fetch(k16);
                        uint32_t res[4];
#pragma unroll
                        for (int j = 0; j < 4; j++)
                            res[j] = add2(add2(add2((&v[0].x)[j], (&v[1].x)[j]), add2((&v[2].x)[j], (&v[3].x)[j])), add2((&v[4].x)[j], b2));
                        const uint32_t dst = stg + 18432 + (c & 1) * 4096 + k16;
                        sts128(dst, res[0], res[1], res[2], res[3]);
                    }
                    if (c == 1 && hl == 0) CSTAMP(25);
                    fence_async_smem();
                    __syncwarp();
                    if (lane == 0) mbar_arrive(bars + B_SFREE * 8);
                    if (c == 1 && hl == 0) CSTAMP(26);
                    if (c == 3) bar_sync<11, 224>(); else bar_sync<3, 96>();
                    if (hl == 0) {
                        bulk_store(g_y + 8 + (size_t)(blockIdx.x * 4 + c) * 256, sc + OFF_STG + 18432 + (c & 1) * 4096, 4096);
                        asm volatile("cp.async.bulk.commit_group;" ::: "memory");
                        STAMP(10 + c);
                    }
                    __syncwarp();
                }
#pragma unroll 1
                for (int k = c < 0 ? 0 : c + 2; k < c + 3 && k < 4; k++) {
                    if (k > 0) mbar_wait(bars + B_WFREE * 8, (k - 1) & 1);
                    mbar_wait(bars + (B_U + (k & 1)) * 8, k >> 1);
                    if (hl < 65) conv_windows(sb + OFF_U + (k & 1) * UCH + (128 - hl) * 16, sb + OFF_W + hl * 16, hl);
                    fence_async_smem();
                    __syncwarp();
                    if (lane == 0) mbar_arrive(bars + B_WRDY * 8);
                    if (k == 0 && warp != 13) {
                        const int hf = warp - 14, lane = fresh_tid() & 31, ti = tile_i() + (fresh_tid() >> 10), tj = tile_j() + (fresh_tid() >> 10);
                        const uint2 b1 = ldg64(p.b1 + tj * BF + (lane < 28 ? lane : 0) * 8 + hf * 4);
                        mbar_wait(bars + B_PRO2 * 8, 0);
                        const uint32_t ep = lds32(epoch_addr);
                        if (hf && lane == 0) wait_flag(g_cnt(2), (ep + 1u) * NCTA);
                        __syncwarp();
                        bar_sync<0, 64>();
                        const uint4 r0 = ld_relaxed128((const uint4*)(g_stats + ti * 128) + hf * 32 + lane);
                        const uint4* cs = (const uint4*)(g_colsum + tj * BF + (lane < 28 ? lane : 0) * 8) + hf;
                        uint4 c[4];
#pragma unroll
                        for (int r = 0; r < 4; r++) c[r] = ld_relaxed128(cs + r * (F_ / 4));
                        float t[4];
#pragma unroll
                        for (int k = 0; k < 4; k++) t[k] = (__uint_as_float((&c[0].x)[k]) + __uint_as_float((&c[1].x)[k])) + (__uint_as_float((&c[2].x)[k]) + __uint_as_float((&c[3].x)[k]));
                        if (lane < 28) {
                            sts128f(sb + OFF_VEC + lane * 64 + hf * 32, t[0], 0.5f * bf_lo(b1.x), t[1], 0.5f * bf_hi(b1.x));
                            sts128f(sb + OFF_VEC + lane * 64 + hf * 32 + 16, t[2], 0.5f * bf_lo(b1.y), t[3], 0.5f * bf_hi(b1.y));
                        }
                        sts128(sb + OFF_RST + hf * 512 + lane * 16, r0.x, r0.y, r0.z, r0.w);
                        if (hf && lane == 0) sts32(stg + 26624 + 32, ep);
                        __syncwarp();
                        if (lane == 0) { mbar_arrive(bars + B_VEC * 8); if (hf) STAMP(29); }
                    }
                }
            }
            if (hl == 0) {
                asm volatile("cp.async.bulk.wait_group 0;" ::: "memory");
                asm volatile("red.global.add.u32 [%0], 1;" ::"l"(g_cnt(8 + (blockIdx.x >> 4))) : "memory");
                STAMP(14);
            }
            if (hl == 64) {
                wait_flag(g_cnt(8 + tj), (lds32(stg + 26624 + 32) + 1u) * 16u);
                mbar_wait(bars + B_PRO * 8, 1);
                mbar_expect_tx(bars + B_CONV * 8, 16384);
                tma_load_3d(sc + 7 * SLOT, &tmY, bars + B_CONV * 8, (120 - 8 * ti) * 8, tj * 64, 0);
            }
        }
    } else if (role == 2) {
        const int ctid = threadIdx.x - 256, lane = ctid & 31, w = ctid >> 5, g = lane >> 2, q = lane & 3, cta = blockIdx.x;
        {
            const int chl = ctid >> 6, nl = ctid & 63;
            const uint32_t pw[2][6] = {{er[0], er[1], er[2], er[3], er[4], er[5]}, {er[8], er[9], er[10], er[11], er[12], er[13]}}, ldt[2] = {er[6], er[14]};
            if constexpr (REG_CONV > 128) asm volatile("setmaxnreg.inc.sync.aligned.u32 %0;" ::"n"(REG_CONV));
            else if constexpr (REG_CONV < 128) asm volatile("setmaxnreg.dec.sync.aligned.u32 %0;" ::"n"(REG_CONV));
            sched_fence();
            float kacc[2][20], k0[2] = {0.f, 0.f};
            const float dt0 = bf_round(ex2f(bf_lo(ldt[0]) * 1.4426950408889634f)), dt1 = bf_round(ex2f(bf_lo(ldt[1]) * 1.4426950408889634f));
#pragma unroll
            for (int k = 0; k < 20; k++) kacc[0][k] = 0.f;
            {
                cplx c, z1, z256;
                auto seeds = [&](int rr) {
                    const bool pr = rr >= 2;
                    const float dt = pr ? dt1 : dt0;
                    const int sh = (rr & 1) ? 0 : 16;
                    float pv[6];
#pragma unroll
                    for (int k = 0; k < 6; k++) pv[k] = __uint_as_float(((pr ? pw[1][k] : pw[0][k]) << sh) & 0xffff0000u);
                    const float a2 = (dt * pv[0]) * 1.4426950408889634f;
                    const float bb = dt * pv[1];
                    const float rh = bb * 0.15915494f;
                    const float rev = (rh - rintf(rh)) + (fmaf(bb, 0.15915494f, -rh) + bb * 6.420638e-9f);
                    c = cmul({pv[4], pv[5]}, {dt * pv[2], dt * pv[3]});
                    z1 = zpow(a2, rev, 1.f);
                    z256 = zpow(a2, rev, 256.f);
                };
                if (ctid == 0) KSTAMP(21);
#pragma unroll 1
                for (int pr = 0; pr < 2; pr++) {
#pragma unroll
                  for (int r = 0; r < 2; r++) {
                    const int rr = 2 * pr + r;
                    seeds(rr);
                    if (r == 0) { wg_wait<0>(); bar_sync<2, 128>(); }
                    k0[0] += rr < 2 ? c.r : 0.f; k0[1] += rr < 2 ? 0.f : c.r;
                    const cplx z2 = csq(z1), z8 = csq(csq(z2));
                    const uint32_t sa = sb + OFF_KST + r * KSTAGE + nl * 16;
                    {
                        const cplx q2 = csq(z8), q3 = cmul(q2, z8), q4 = csq(q2), q5 = cmul(q4, z8), q6 = csq(q3), q7 = cmul(q4, q3);
                        const uint32_t qr[4] = {pack_bf16(1.f, z8.r), pack_bf16(q2.r, q3.r), pack_bf16(q4.r, q5.r), pack_bf16(q6.r, q7.r)};
                        const uint32_t qi[4] = {pack_bf16(0.f, z8.i), pack_bf16(q2.i, q3.i), pack_bf16(q4.i, q5.i), pack_bf16(q6.i, q7.i)};
                        const uint32_t ad = sa + chl * 4 * 2048;
                        sts128(ad, qr[0], qr[1], qr[2], qr[3]);
                        sts128(ad + 1024, qi[0], qi[1], qi[2], qi[3]);
                        const cplx p1 = csq(q4), p2 = csq(p1), p3 = cmul(p2, p1);
#pragma unroll
                        for (int gq = 1; gq < 4; gq++) {
                            const cplx pa = gq == 1 ? p1 : gq == 2 ? p2 : p3;
                            const uint32_t pr2 = pack_bf16(pa.r, pa.r), pi2 = pack_bf16(pa.i, pa.i), ni2 = pack_bf16(-pa.i, -pa.i);
                            uint32_t re[4], im[4];
#pragma unroll
                            for (int k = 0; k < 4; k++) { re[k] = fma2(qr[k], pr2, mul2(qi[k], ni2)); im[k] = fma2(qi[k], pr2, mul2(qr[k], pi2)); }
                            sts128(ad + gq * 2048, re[0], re[1], re[2], re[3]);
                            sts128(ad + gq * 2048 + 1024, im[0], im[1], im[2], im[3]);
                        }
                    }
                    {
                        const cplx z1c = {z1.r, -z1.i}, z256c = {z256.r, -z256.i}, cc = {c.r, -c.i};
                        const cplx z2c = {z2.r, -z2.i};
                        cplx hh[8];
                        hh[0] = cmul(cc, z1c); hh[1] = cmul(cc, z2c);
#pragma unroll
                        for (int k = 2; k < 8; k++) hh[k] = cmul(hh[k - 2], z2c);
                        const uint32_t ad = sa + 16384 + chl * 3 * 2048;
                        sts128(ad, pack_bf16(hh[0].r, hh[1].r), pack_bf16(hh[2].r, hh[3].r), pack_bf16(hh[4].r, hh[5].r), pack_bf16(hh[6].r, hh[7].r));
                        sts128(ad + 1024, pack_bf16(hh[0].i, hh[1].i), pack_bf16(hh[2].i, hh[3].i), pack_bf16(hh[4].i, hh[5].i), pack_bf16(hh[6].i, hh[7].i));
                        const cplx z512c = csq(z256c);
                        const cplx c2 = cmul(hh[1], z256c), c4 = cmul(hh[3], z256c), c6 = cmul(hh[5], z256c), c8 = cmul(hh[7], z256c);
                        const cplx d4 = cmul(hh[3], z512c), d8 = cmul(hh[7], z512c), f4 = cmul(c4, z512c), f8 = cmul(c8, z512c);
                        sts128(ad + 2048, pack_bf16(c2.r, c4.r), pack_bf16(c6.r, c8.r), pack_bf16(d4.r, d8.r), pack_bf16(f4.r, f8.r));
                        sts128(ad + 3072, pack_bf16(c2.i, c4.i), pack_bf16(c6.i, c8.i), pack_bf16(d4.i, d8.i), pack_bf16(f4.i, f8.i));
                        const cplx e0 = cmul(d8, z512c), e1 = cmul(f8, z512c), e2 = cmul(e0, z512c), e3 = cmul(e1, z512c);
                        const uint32_t ae = sa + 16384 + 4096 + chl * 8;
                        sts64(ae, pack_bf16(e0.r, e1.r), pack_bf16(e2.r, e3.r));
                        sts64(ae + 1024, pack_bf16(e0.i, e1.i), pack_bf16(e2.i, e3.i));
                    }
                  }
                    fence_async_smem();
                    wg_wait<0>();
                    bar_sync<2, 128>();
                    if (pr) {
#pragma unroll
                        for (int k = 0; k < 20; k++) kacc[0][k] = kacc[1][k];
                    }
                    constexpr uint64_t da = make_desc(sd + OFF_KST, 128, 2048, 0);
                    wg_fence();
                    static_for<16>([&](auto ks) {
                        constexpr int o = (ks / 8) * (KSTAGE / 16) + (ks % 8) * 16;
                        wgmma_ss_mn40<o, o + 1024>(kacc[1], da, da, ks != 0);
                    });
                    wg_commit();
                }
#pragma unroll
                for (int o = 16; o > 0; o >>= 1) { k0[0] += __shfl_xor_sync(0xffffffffu, k0[0], o); k0[1] += __shfl_xor_sync(0xffffffffu, k0[1], o); }
            }
            bar_sync<6, 160>();
            wg_wait<0>();
            if constexpr (!GATE_LATE) asm volatile("bar.arrive 8, 384;" ::: "memory");
            bar_sync<2, 128>();
            if (ctid == 0) KSTAMP(26);
#pragma unroll
            for (int pr = 0; pr < 2; pr++) {
                const float* ka = kacc[pr];
                float v[8];
#pragma unroll
                for (int k = 0; k < 8; k++) v[k] = (w >> 1) ? ka[12 + k] : ka[k];
                const uint32_t kc = sb + OFF_STG + (pr * 2 + (w >> 1)) * KC_BYTES + 4;
                if (lane == 0) sts32(kc - (w & 1) * 4, __float_as_uint(k0[pr]));
#pragma unroll
                for (int hf = 0; hf < 2; hf++) {
                    const int j = 16 * (w & 1) + g + 8 * hf;
                    sts64f(kc + (8 * j + 2 * q + 1) * 4, v[2 * hf], v[2 * hf + 1]);
                    sts64f(kc + (q < 2 ? 256 + 4 * j + 2 * q + 1 : 256 + 64 * q + 2 * j + 1) * 4, v[4 + 2 * hf], v[5 + 2 * hf]);
                    if ((q >> 1) == (w >> 1)) {
                        sts32(kc + (512 + 64 * (q & 1) + j + 1) * 4, __float_as_uint(ka[8 + 2 * hf]));
                        sts32(kc + (544 + 64 * (q & 1) + j + 1) * 4, __float_as_uint(ka[9 + 2 * hf]));
                    }
                }
            }
            bar_sync<2, 128>();
            if (ctid == 0) KSTAMP(27);
            const uint32_t kc = sb + OFF_STG + w * KC_BYTES + 4;
            const uint32_t tw = sb + OFF_TW + w * TW_BYTES + TW_OFF * 4;
            const uint32_t te = sb + OFF_TE + w * 1024;
            float2 ab[10], pe[2];
            float kp[8];
#pragma unroll
            for (int s = 0; s < 10; s++) ab[s] = lds64f(kc + (64 * s + 2 * lane + 1) * 4);
#pragma unroll
            for (int s = 0; s < 8; s++) kp[s] = __uint_as_float(lds32(kc + (64 * s + 2 * lane) * 4));
#pragma unroll
            for (int s = 0; s < 2; s++) pe[s] = lds64f(kc + (511 + 64 * s + 2 * lane) * 4);
            const float k0b = __uint_as_float(lds32(kc - 4)), k1024 = __uint_as_float(lds32(kc + 512 * 4));
            if (lane == 0) { kp[0] += k0b; pe[0] = make_float2(0.f, 0.f); }
#pragma unroll
            for (int set = 0; set < 2; set++) {
                const int pi = 32 * set + lane;
                {
                    const float ka = ab[4 + set].x, kb = ab[4 + set].y, k_ = kp[4 + set];
                    const uint32_t pp = pack_bf16(k_, k_);
                    sts128(tw + (256 + 4 * pi) * 4, pp, pp, pack_bf16(ka, k_), pack_bf16(kb, ka));
                }
                {
                    const float ka = ab[6 + set].x, kb = ab[6 + set].y, k_ = kp[6 + set];
                    const uint32_t pp = pack_bf16(k_, k_), aa = pack_bf16(ka, ka);
                    sts128(tw + (512 + 8 * pi) * 4, pp, pp, pp, pack_bf16(ka, k_));
                    sts128(tw + (512 + 8 * pi) * 4 + 16, aa, aa, pack_bf16(kb, ka), pack_bf16(kb, kb));
                }
                sts32(te + (64 + pi) * 4, pack_bf16(ab[8 + set].y, pe[set].y));
                sts32(te + 512 + (64 + pi) * 4, pack_bf16(ab[8 + set].x, pe[set].x));
                sts64(te + set * 512 + lane * 8, 0u, 0u);
            }
            {
                const uint32_t pp = pack_bf16(k1024, k1024);
                sts64(tw + (1024 + 2 * lane) * 4, lane <= 2 ? pp : 0u, lane < 2 ? pp : lane == 2 ? (pp & 0xffff0000u) : 0u);
                sts32(tw - TW_OFF * 4 + lane * 4, 0u);
                if (lane == 0) { kp[0] += bf_lo(er[7]); sts32(tw, pack_bf16(kp[0], 0.f)); }
            }
            __syncwarp();
#pragma unroll
            for (int s = 0; s < 4; s++) {
                const int x = 64 * s + 2 * lane + 1;
                sts32(tw + x * 4, pack_bf16(ab[s].x, kp[s]));
                sts32(tw + x * 4 + 4, pack_bf16(ab[s].y, ab[s].x));
            }
        }
        if (ctid < 4) sts32(sb + OFF_STG + 26624 + ctid * 4, er[15] * 0x10001u);
        bar_sync<2, 128>();
        if (lane < 2 * w) sts128(sb + OFF_STG + w * 4096 + (lane & 1) * 2048 + (127 - (lane >> 1)) * 16, 0u, 0u, 0u, 0u);
        if (ctid == 0) mbar_arrive(bars + B_TAB * 8);
        if constexpr (GATE_LATE) asm volatile("bar.arrive 8, 384;" ::: "memory");
        if (ctid == 0) STAMP(8);
#pragma unroll 1
        for (int c = 0; c < 4; c++) {
            float d[64], d3[8];
            uint32_t a[NBUF][CB][4];
            ConvCtx cx;
            cx.tw = sb + OFF_TW + c * TW_BYTES + (TW_OFF + 16 * w + g - 2 * q) * 4;
            cx.te = sb + OFF_TE + c * 1024 + (64 + 16 * w + g - 2 * q) * 4;
            cx.zero = threadIdx.x >> 10;
            cx.du = make_desc(sd + OFF_U + (c & 1) * UCH, PLANE, 128, 0);
            cx.dw = make_desc(sd + OFF_W, 128, 1024, 0);
            cx.wbar = bars + B_WRDY * 8;
            cx.wpar = c & 1;
            cx.last = c == 3;
            cx.dbg = c == VCH;
            if (CONV_PAUSE && c == 1) bar_sync<9, 384>();
            static_for<NBUF - 1>([&](auto i) { conv_load<i>(a[i], cx); });
            mbar_wait(bars + (B_U + (c & 1)) * 8, c >> 1);
            if (ctid == 0 && c == VCH) VSTAMP(22);
            ConvBatches<0>::run(d, d3, a, cx);
            if (ctid == 0 && c == VCH) VSTAMP(25);
            if (c > 0) mbar_wait(bars + B_SFREE * 8, (c - 1) & 1);
            if (ctid == 0 && c == VCH) VSTAMP(26);
            wg_wait<0>();
            if (ctid == 0 && c == VCH) VSTAMP(27);

            const uint32_t stg = sb + OFF_STG;
            const int n0 = (lane >> 4) * 8 + (lane & 7) - w;
            const uint32_t sa = stg + w * 4096 + ((lane >> 3) & 1) * 2048 + n0 * 16;
#pragma unroll
            for (int jj = 0; jj < 8; jj++)
                stsm_x4_t(jj == 0 && n0 < 0 ? sb + OFF_VEC - 16 : sa + jj * 256, pack_bf16(d[8 * jj], d[8 * jj + 1]), pack_bf16(d[8 * jj + 2], d[8 * jj + 3]),
                          pack_bf16(d[8 * jj + 4], d[8 * jj + 5]), pack_bf16(d[8 * jj + 6], d[8 * jj + 7]));
            stsm_x4(stg + 16384 + (lane >> 4) * 1024 + (63 - 16 * w - (lane & 15)) * 16,
                    pack_bf16(d3[0], d3[1]), pack_bf16(d3[2], d3[3]), pack_bf16(d3[4], d3[5]), pack_bf16(d3[6], d3[7]));
            __syncwarp();
            if (lane == 0) mbar_arrive(bars + B_SFULL * 8);
            if (ctid == 0 && c == 1) VSTAMP(21);
            if (ctid == 0 && c == VCH) VSTAMP(16);
        }
        {
            mbar_wait(bars + B_SFULL * 8, 1);
            const uint32_t k16 = (96 + ctid) * 16, sa = sb + OFF_STG + k16, b2 = lds32(sb + OFF_STG + 26624 + 12);
            uint4 v[5];
#pragma unroll
            for (int ww = 0; ww < 4; ww++) v[ww] = lds128(sa + ww * 4096);
            v[4] = lds128((k16 & 1024) ? sb + OFF_U + 2048 : sa + 16384 - ((k16 >> 1) & 1024));
            uint32_t res[4];
#pragma unroll
            for (int j = 0; j < 4; j++) res[j] = add2(add2(add2((&v[0].x)[j], (&v[1].x)[j]), add2((&v[2].x)[j], (&v[3].x)[j])), add2((&v[4].x)[j], b2));
            sts128(sa + 18432 + 4096, res[0], res[1], res[2], res[3]);
            fence_async_smem();
            asm volatile("bar.arrive 11, 224;" ::: "memory");
        }
    } else {
        const int tid = threadIdx.x, lane = tid & 31, warp = tid >> 5;
        const int ti = tile_i(), tj = tile_j();
        const int wg = role, w = warp & 3, g = lane >> 2, q = lane & 3;
        {
            const uint4 xv[2][2] = {{{er[0], er[1], er[2], er[3]}, {er[4], er[5], er[6], er[7]}}, {{er[8], er[9], er[10], er[11]}, {er[12], er[13], er[14], er[15]}}};
            uint2 xc[8];
#pragma unroll
            for (int r = 0; r < 8; r++) xc[r] = make_uint2(er[16 + 2 * r], er[17 + 2 * r]);
            asm volatile("setmaxnreg.inc.sync.aligned.u32 %0;" ::"n"(REG_MLP));
            float s1[2], s2[2], sh[2];
#pragma unroll
            for (int r = 0; r < 2; r++) sh[r] = bf_lo(__shfl_sync(0xffffffffu, xv[r][0].x, 0));
#pragma unroll
            for (int r = 0; r < 2; r++) {
                const uint32_t raw[8] = {xv[r][0].x, xv[r][0].y, xv[r][0].z, xv[r][0].w, xv[r][1].x, xv[r][1].y, xv[r][1].z, xv[r][1].w};
                float a[4] = {0.f, 0.f, 0.f, 0.f}, b[4] = {0.f, 0.f, 0.f, 0.f};
#pragma unroll
                for (int k = 0; k < 8; k++) {
                    const float t0 = bf_lo(raw[k]) - sh[r], t1 = bf_hi(raw[k]) - sh[r];
                    a[k & 3] += t0 + t1;
                    b[k & 3] = fmaf(t0, t0, fmaf(t1, t1, b[k & 3]));
                }
                s1[r] = (a[0] + a[1]) + (a[2] + a[3]);
                s2[r] = (b[0] + b[1]) + (b[2] + b[3]);
            }
#pragma unroll
            for (int o = 16; o > 0; o >>= 1) {
#pragma unroll
                for (int r = 0; r < 2; r++) { s1[r] += __shfl_xor_sync(0xffffffffu, s1[r], o); s2[r] += __shfl_xor_sync(0xffffffffu, s2[r], o); }
            }
            if (lane < 2) {
                const float md = (lane ? s1[1] : s1[0]) * (1.f / D_);
                const float var = fmaxf(fmaf(-md, md, (lane ? s2[1] : s2[0]) * (1.f / D_)), 0.f);
                const float mean = md + (lane ? sh[1] : sh[0]);
                const float m1 = bf_round(mean);
                const float r1 = rcp_fast(bf_round(sqrt_fast(bf_round(bf_round(var) + 1e-5f))));
                const float rh = bf_round(r1);
                sts128(sb + OFF_RST + 384 + (lane * 8 + warp) * 16, pack_bf16(-m1, -m1), pack_bf16(rh, rh), pack_bf16(r1 - rh, r1 - rh), 0u);
                const float m2 = bf_round((mean - m1) * r1);
                const float r2 = rcp_fast(bf_round(sqrt_fast(bf_round(bf_round(var * r1 * r1) + 1e-5f))));
                sts64f(sb + OFF_RST + 256 + (lane * 8 + warp) * 8, 0.5f * r1 * r2, -0.5f * (m1 * r1 + m2) * r2);
            }
            if (tid == 0) STAMP(19);
            bar_sync<5, 288>();
#pragma unroll
            for (int r = 0; r < 8; r++) {
                const uint4 ms = lds128(sb + OFF_RST + 384 + ((tid & 1) * 8 + r) * 16);
                const uint32_t d0 = add2(xc[r].x, ms.x), d1 = add2(xc[r].y, ms.x);
                xc[r].x = fma2(d0, ms.y, mul2(d0, ms.z));
                xc[r].y = fma2(d1, ms.y, mul2(d1, ms.z));
            }
            const uint32_t dst = sb + (NSLOT - 1) * SLOT + tid * 16;
            sts128(dst, __byte_perm(xc[0].x, xc[1].x, 0x5410), __byte_perm(xc[2].x, xc[3].x, 0x5410), __byte_perm(xc[4].x, xc[5].x, 0x5410), __byte_perm(xc[6].x, xc[7].x, 0x5410));
            sts128(dst + 4096, __byte_perm(xc[0].x, xc[1].x, 0x7632), __byte_perm(xc[2].x, xc[3].x, 0x7632), __byte_perm(xc[4].x, xc[5].x, 0x7632), __byte_perm(xc[6].x, xc[7].x, 0x7632));
            sts128(dst + 8192, __byte_perm(xc[0].y, xc[1].y, 0x5410), __byte_perm(xc[2].y, xc[3].y, 0x5410), __byte_perm(xc[4].y, xc[5].y, 0x5410), __byte_perm(xc[6].y, xc[7].y, 0x5410));
            sts128(dst + 12288, __byte_perm(xc[0].y, xc[1].y, 0x7632), __byte_perm(xc[2].y, xc[3].y, 0x7632), __byte_perm(xc[4].y, xc[5].y, 0x7632), __byte_perm(xc[6].y, xc[7].y, 0x7632));
            fence_async_smem();
            __syncwarp();
            if (lane == 0) mbar_arrive(bars + B_PRO * 8);
            if (tid == 0) STAMP(0);
        }
        auto my_turn = [&]() { if (wg == 0) bar_sync<12, 256>(); else bar_sync<13, 256>(); };
        auto your_turn = [&]() { if (wg == 0) asm volatile("bar.arrive 13, 256;" ::: "memory"); else asm volatile("bar.arrive 12, 256;" ::: "memory"); };
        if (PINGPONG && wg == 1) your_turn();
        uint32_t h[56];
        {
            float acc[112];
            const uint64_t da = make_desc(sd + wg * 8192, 16, 1024, 1), db = make_desc(sd, 8192, 1024, 1);
            static_for<8>([&](auto KB) {
                constexpr int kb = KB, sX = (3 * kb) % NSLOT, sA = (3 * kb + 1) % NSLOT, sB = (3 * kb + 2) % NSLOT;
                if constexpr (kb == GATE_KB) bar_sync<8, 384>();
                mbar_wait(bars + (B_FULL + sX) * 8, ((3 * kb) / NSLOT) & 1);
                mbar_wait(bars + (B_FULL + sA) * 8, ((3 * kb + 1) / NSLOT) & 1);
                if (kb == 0 && tid == 0) STAMP(1);
                if (PINGPONG & 1) my_turn();
                wg_fence();
                static_for<4>([&](auto ks) { wgmma_ss_kn128<sX * (SLOT / 16) + ks * 2, sA * (SLOT / 16) + ks * 128>(acc, da, db, ks != 0 || kb != 0); });
                wg_commit();
                if ((PINGPONG & 5) == 5) your_turn();
                if constexpr (kb > 0) {
                    wg_wait<1>();
                    if (lane == 0) {
                        if constexpr (3 * kb - 3 < 16 || 3 * kb - 3 > 19) mbar_arrive(bars + (B_EMPTY + (3 * kb + 7) % NSLOT) * 8);
                        if constexpr (3 * kb - 1 < 16 || 3 * kb - 1 > 19) mbar_arrive(bars + (B_EMPTY + (3 * kb + 9) % NSLOT) * 8);
                    }
                }
                mbar_wait(bars + (B_FULL + sB) * 8, ((3 * kb + 2) / NSLOT) & 1);
                if ((PINGPONG & 5) == 5) my_turn();
                wg_fence();
                static_for<4>([&](auto ks) { wgmma_ss_kn96<sX * (SLOT / 16) + ks * 2, sB * (SLOT / 16) + ks * 128>(acc + 64, da, db, ks != 0 || kb != 0); });
                wg_commit();
                if (PINGPONG & 1) your_turn();
                wg_wait<1>();
                if constexpr (3 * kb + 1 < 16 || 3 * kb + 1 > 19) { if (lane == 0) mbar_arrive(bars + (B_EMPTY + sA) * 8); }
            });
            mbar_wait(bars + B_VEC * 8, 1);
            const uint32_t sta = sb + OFF_RST + ((warp >> 1) * 32 + ((warp & 1) ^ 1) * 8 + g) * 8;
            const float2 st0 = lds64f(sta), st1 = lds64f(sta + 128);
            wg_wait<0>();
            if (lane == 0) {
                mbar_arrive(bars + (B_EMPTY + 21 % NSLOT) * 8); mbar_arrive(bars + (B_EMPTY + 23 % NSLOT) * 8);
                if (wg) asm volatile("mbarrier.arrive.shared::cta.b64 _, [%0], 7;" ::"r"(bars + (B_EMPTY + 6 + w) * 8) : "memory");
                mbar_expect_tx(bars + ((wg ? B_EMPTY : B_FULL) + 6 + w) * 8, 8192);
                asm volatile("mbarrier.arrive.shared::cluster.b64 _, [%0];" ::"r"(map_peer(bars + B_PEER * 8)) : "memory");
            }
            if (tid == 0) STAMP(2);
#pragma unroll
            for (int j4 = 0; j4 < 14; j4++) {
                float y[8], t[8];
#pragma unroll
                for (int jj = 0; jj < 2; jj++) {
                    const float4 sv = lds128f(sb + OFF_VEC + (16 * j4 + 8 * jj + 2 * q) * 8);
                    const float* a4 = acc + 8 * j4 + 4 * jj;
                    y[4 * jj] = fmaf(st0.x, a4[0], fmaf(st0.y, sv.x, sv.y)); y[4 * jj + 1] = fmaf(st0.x, a4[1], fmaf(st0.y, sv.z, sv.w));
                    y[4 * jj + 2] = fmaf(st1.x, a4[2], fmaf(st1.y, sv.x, sv.y)); y[4 * jj + 3] = fmaf(st1.x, a4[3], fmaf(st1.y, sv.z, sv.w));
                }
#pragma unroll
                for (int k = 0; k < 8; k++) t[k] = tanh_fast(y[k] * fmaf(y[k] * y[k], 0.2854192648f, 1.5957691216f));
#pragma unroll
                for (int k = 0; k < 4; k++) h[4 * j4 + k] = pack_bf16(fmaf(y[2 * k], t[2 * k], y[2 * k]), fmaf(y[2 * k + 1], t[2 * k + 1], y[2 * k + 1]));
                if (j4 % 3 == 2) sched_fence();
            }
        }
        if (CONV_PAUSE) asm volatile("bar.arrive 9, 384;" ::: "memory");
        if (tid == 0) STAMP(3);

        float acc[32];
        uint32_t sum[16];
        uint32_t pk[16];
        const int wtid = tid & 127;
        uint4 v[4];
        uint4* const pbase = g_part + (unsigned)(ti * PART_I + 8 + wg * 512 + wtid);
        auto gather_issue = [&](uint4* v, int u) {
            const uint4* ps = pbase + (unsigned)((tj * 3 + u) * 1024);
#pragma unroll
            for (int c = 0; c < 4; c++) v[c] = ld_relaxed128(ps + c * 128);
        };
        const uint32_t pm = (lds32(sb + OFF_STG + 26624 + 32) & 1u) - 1u;
        auto consume = [&](uint4* v, int u) {
#pragma unroll 1
            for (int it = 0; it < SPIN_LIMIT; it++) {
                uint32_t b8[8];
#pragma unroll
                for (int c = 0; c < 4; c++) { b8[2 * c] = lop3<0x7e>(v[c].x, v[c].y, pm); b8[2 * c + 1] = lop3<0x7e>(v[c].z, v[c].w, pm); }
                const uint32_t bad = lop3<0xfe>(lop3<0xfe>(b8[0], b8[1], b8[2]), lop3<0xfe>(b8[3], b8[4], b8[5]), b8[6] | b8[7]);
                if (!(bad & 1u)) break;
                gather_issue(v, u);
            }
#pragma unroll
            for (int c = 0; c < 16; c++) sum[c] = u == 0 ? (&v[c >> 2].x)[c & 3] : add2(sum[c], (&v[c >> 2].x)[c & 3]);
        };
        const uint64_t dbase = make_desc(sd, 8192, 1024, 1);
        const uint32_t toff = sb + 6 * SLOT + wg * 8192 + wtid * 16;
        const uint32_t lbar = bars + ((wg ? B_EMPTY : B_FULL) + 6) * 8, rbar = map_peer(lbar);
        static_for<8>([&](auto S) {
            constexpr int s = S, slot = (4 + 2 * s) % 6, pslot = (4 + 2 * s + 4) % 6;
            constexpr bool adds = s >= 3 && s <= 5, sent = s == 1 || s == 2 || s == 3 || s == 7;
            constexpr int sbuf = s == 7 ? 3 : s - 1;
            if constexpr (s > 0) {
                if constexpr (adds) mbar_wait(lbar + (s - 3) * 8, s < 5 ? wg : 0);
                wg_wait<0>();
                if (tid == 0) GSTAMP(20 + s);
                if constexpr (s < 6) { if (lane == 0) { mbar_arrive(bars + (B_EMPTY + pslot) * 8); mbar_arrive(bars + (B_EMPTY + pslot + 1) * 8); } }
#pragma unroll
                for (int c = 0; c < 16; c++) {
                    pk[c] = pack_bf16(acc[2 * c], acc[2 * c + 1]);
                    if constexpr (!sent) pk[c] = lop3<0xd8>(pk[c], pm, 1u);
                }
            }
            if constexpr (adds) {
#pragma unroll
                for (int c = 0; c < 4; c++) {
                    const uint4 t = lds128(toff + (s - 3) * SLOT + c * 2048);
                    acc[8 * c] = bf_lo(t.x); acc[8 * c + 1] = bf_hi_fast(t.x); acc[8 * c + 2] = bf_lo(t.y); acc[8 * c + 3] = bf_hi_fast(t.y);
                    acc[8 * c + 4] = bf_lo(t.z); acc[8 * c + 5] = bf_hi_fast(t.z); acc[8 * c + 6] = bf_lo(t.w); acc[8 * c + 7] = bf_hi_fast(t.w);
                }
            }
            if constexpr (s == 4) { __syncwarp(); if (lane == 0) mbar_arrive(bars + B_PRO * 8); }
            if constexpr (s == YIELD_STEP) bar_sync<10, 384>();
            constexpr int fpar = ((slot < 4 ? 1 : 0) + s / 3) & 1;
            mbar_wait(bars + (B_FULL + slot) * 8, fpar);
            mbar_wait(bars + (B_FULL + slot + 1) * 8, fpar);
            if constexpr (s == 7) { if (tid == 0) GSTAMP(16); }
            if (PINGPONG & 2) my_turn();
            wg_fence();
            static_for<14>([&](auto ks) {
                constexpr int o = (slot + ks / 7) * (SLOT / 16) + (ks % 7) * 128;
                if constexpr (s >= SMALL_FROM) {
                    wgmma_rs_n32<o>(acc, h[4 * ks], h[4 * ks + 1], h[4 * ks + 2], h[4 * ks + 3], dbase, ks != 0 || adds);
                    wgmma_rs_n32<o + 4>(acc + 16, h[4 * ks], h[4 * ks + 1], h[4 * ks + 2], h[4 * ks + 3], dbase, ks != 0 || adds);
                } else {
                    wgmma_rs_n64<o>(acc, h[4 * ks], h[4 * ks + 1], h[4 * ks + 2], h[4 * ks + 3], dbase, ks != 0 || adds);
                }
            });
            wg_commit();
            if ((PINGPONG & 2) && (s < 7 || wg == 0)) your_turn();
            if constexpr (s == 7) { if (tid == 0) GSTAMP(18); }
            if constexpr (s == 7) consume(v, 0);
            if constexpr (s == 7) { if (tid == 0) GSTAMP(9); }
            if constexpr (s >= 6) gather_issue(v, s - 6);
            if constexpr (s == 0) {
                mbar_wait(bars + B_PEER * 8, 0);
            } else if constexpr (sent) {
                const uint32_t rtoff = map_peer(toff);
#pragma unroll
                for (int c = 0; c < 4; c++)
                    asm volatile("st.async.weak.shared::cluster.mbarrier::complete_tx::bytes.v4.u32 [%0], {%1, %2, %3, %4}, [%5];"
                                 ::"r"(rtoff + sbuf * SLOT + c * 2048), "r"(pk[4 * c]), "r"(pk[4 * c + 1]), "r"(pk[4 * c + 2]), "r"(pk[4 * c + 3]), "r"(rbar + sbuf * 8) : "memory");
            } else {
                uint4* dst = pbase + (unsigned)((block_of_step(tj, s - 1) * 3 + (s - 4)) * 1024);
#pragma unroll
                for (int c = 0; c < 4; c++) st_relaxed128(dst + c * 128, pk[4 * c], pk[4 * c + 1], pk[4 * c + 2], pk[4 * c + 3]);
            }
        });
        if (tid == 0) STAMP(4);
        consume(v, 1);
        gather_issue(v, 2);
        consume(v, 2);
        if (tid == 0) GSTAMP(5);
        {
            mbar_wait(lbar + 24, 0);
#pragma unroll
            for (int c = 0; c < 4; c++) {
                const uint4 t = lds128(toff + 3 * SLOT + c * 2048);
#pragma unroll
                for (int k = 0; k < 4; k++) sum[4 * c + k] = add2(sum[4 * c + k], (&t.x)[k]);
            }
            const uint32_t stg = sb + 6 * SLOT + wg * 8192;
            const uint32_t t = fresh_tid();
            const uint32_t xa = stg + (((t >> 5) & 3) * 16 + (t & 15)) * 128, xs = ((t >> 4) & 1) ^ (t & 7);
            const uint32_t ya = sb + 7 * SLOT + ((t >> 3) & 1) * 8192 + (((t >> 4) & 1) * 8 + (t & 7)) * 128 + (((7 - (t >> 5)) ^ t) & 7) * 16;
            uint32_t xr[16];
            if (tid == 0) GSTAMP(30);
            mbar_wait(bars + (B_FULL + 6) * 8, 1);
#pragma unroll
            for (int jj = 0; jj < 4; jj++) ldsm_x4(xa + ((2 * jj) ^ xs) * 16, xr + 4 * jj);
            wg_wait<0>();
#pragma unroll
            for (int c = 0; c < 16; c++) { acc[2 * c] += bf_lo(sum[c]) + bf_lo(xr[c]); acc[2 * c + 1] += bf_hi_fast(sum[c]) + bf_hi(xr[c]); }
            sched_fence();
            mbar_wait(bars + B_CONV * 8, 0);
#pragma unroll
            for (int jj = 0; jj < 4; jj++) ldsm_x4_t(ya + jj * 2048, pk + 4 * jj);
            if (tid == 0) STAMP(15);
#pragma unroll
            for (int jj = 0; jj < 4; jj++) {
                uint32_t o[4];
#pragma unroll
                for (int k = 0; k < 4; k++) {
                    const int c = 4 * jj + k;
                    o[k] = pack_bf16(acc[2 * c] + bf_lo(pk[c]), acc[2 * c + 1] + bf_hi(pk[c]));
                }
                stsm_x4(xa + ((2 * jj) ^ xs) * 16, o[0], o[1], o[2], o[3]);
            }
            fence_async_smem();
            if (wg == 0) bar_sync<5, 128>(); else bar_sync<4, 128>();
            if ((t & 127) == 0) {
                asm volatile("cp.async.bulk.tensor.2d.global.shared::cta.bulk_group [%0, {%2, %3}], [%1];" ::"l"(&tmO), "r"(sc - sb + stg), "r"(tj * 64), "r"(ti * 128 + wg * 64) : "memory");
                asm volatile("cp.async.bulk.commit_group;" ::: "memory");
                asm volatile("cp.async.bulk.wait_group.read 0;" ::: "memory");
            }
            if (tid == 0) STAMP(7);
            if (tid == 128) STAMP(6);
        }
    }
}

typedef CUresult (*EncodeFn)(CUtensorMap*, CUtensorMapDataType, cuuint32_t, void*, const cuuint64_t*, const cuuint64_t*, const cuuint32_t*,
                             const cuuint32_t*, CUtensorMapInterleave, CUtensorMapSwizzle, CUtensorMapL2promotion, CUtensorMapFloatOOBfill);

extern "C" void kernel_launch(void* const* d_in, const int* in_sizes, int n_in, void* d_out, int out_size) {
    static EncodeFn enc = nullptr;
    if (!enc) {
        void* fp = nullptr;
        cudaDriverEntryPointQueryResult qr;
        cudaGetDriverEntryPoint("cuTensorMapEncodeTiled", &fp, cudaEnableDefault, &qr);
        enc = (EncodeFn)fp;
        cudaFuncSetAttribute(fused_kernel, cudaFuncAttributeMaxDynamicSharedMemorySize, SMEM_BYTES);
    }
    const cuuint32_t es[3] = {1, 1, 1};
    auto mk = [&](CUtensorMap* tm, int rank, void* base, const cuuint64_t* gd, const cuuint64_t* gs, const cuuint32_t* bd) {
        enc(tm, CU_TENSOR_MAP_DATA_TYPE_BFLOAT16, rank, base, gd, gs, bd, es, CU_TENSOR_MAP_INTERLEAVE_NONE, CU_TENSOR_MAP_SWIZZLE_128B,
            CU_TENSOR_MAP_L2_PROMOTION_L2_128B, CU_TENSOR_MAP_FLOAT_OOB_FILL_NONE);
    };
    CUtensorMap tmX, tmW1, tmW2, tmO, tmT, tmC, tmY;
    {
        const cuuint64_t gd[3] = {D_, L_, 1}, gs[2] = {D_ * 2, D_ * 2 * L_};
        const cuuint32_t bd[3] = {64, 128, 1}, bo[2] = {64, 64};
        mk(&tmX, 3, d_in[0], gd, gs, bd);
        mk(&tmO, 2, d_out, gd, gs, bo);
    }
    {
        const cuuint64_t gd[3] = {BF, 8, D_}, gs[2] = {BF * 2, F_ * 2};
        const cuuint32_t bd[3] = {64, 1, 64};
        mk(&tmW1, 3, d_in[10], gd, gs, bd);
    }
    {
        const cuuint64_t gd[3] = {D_, F_, 1}, gs[2] = {D_ * 2, D_ * 2 * F_};
        const cuuint32_t bd[3] = {64, 112, 1};
        mk(&tmW2, 3, d_in[12], gd, gs, bd);
    }
    {
        static void* xt = nullptr;
        if (!xt) cudaGetSymbolAddress(&xt, g_xt);
        const cuuint64_t gd[3] = {L_, 128, 4}, gs[2] = {L_ * 8, L_ * 2};
        const cuuint32_t bd[3] = {16, 128, 4};
        enc(&tmT, CU_TENSOR_MAP_DATA_TYPE_BFLOAT16, 3, xt, gd, gs, bd, es, CU_TENSOR_MAP_INTERLEAVE_NONE, CU_TENSOR_MAP_SWIZZLE_NONE,
            CU_TENSOR_MAP_L2_PROMOTION_NONE, CU_TENSOR_MAP_FLOAT_OOB_FILL_NONE);
    }
    {
        const cuuint64_t gd[3] = {F_, D_, 1}, gs[2] = {F_ * 2, F_ * 2 * D_};
        const cuuint32_t bd[3] = {56, 128, 1};
        enc(&tmC, CU_TENSOR_MAP_DATA_TYPE_BFLOAT16, 3, d_in[10], gd, gs, bd, es, CU_TENSOR_MAP_INTERLEAVE_NONE, CU_TENSOR_MAP_SWIZZLE_NONE,
            CU_TENSOR_MAP_L2_PROMOTION_L2_128B, CU_TENSOR_MAP_FLOAT_OOB_FILL_NONE);
    }
    {
        static void* yp = nullptr;
        if (!yp) cudaGetSymbolAddress(&yp, g_y);
        const cuuint64_t gd[3] = {1024, D_, 2}, gs[2] = {L_ * 2, L_};
        const cuuint32_t bd[3] = {64, 64, 2};
        mk(&tmY, 3, (char*)yp + 128, gd, gs, bd);
    }
    Params p;
    p.x = (const __nv_bfloat16*)d_in[0];
    p.Are = (const __nv_bfloat16*)d_in[1]; p.Aim = (const __nv_bfloat16*)d_in[2];
    p.Bre = (const __nv_bfloat16*)d_in[3]; p.Bim = (const __nv_bfloat16*)d_in[4];
    p.Cre = (const __nv_bfloat16*)d_in[5]; p.Cim = (const __nv_bfloat16*)d_in[6];
    p.logdt = (const __nv_bfloat16*)d_in[7]; p.dskip = (const __nv_bfloat16*)d_in[8];
    p.w1 = (const __nv_bfloat16*)d_in[10]; p.b1 = (const __nv_bfloat16*)d_in[11];
    p.w2 = (const __nv_bfloat16*)d_in[12]; p.b2 = (const __nv_bfloat16*)d_in[13];
    fused_kernel<<<NCTA, NTHREADS, SMEM_BYTES>>>(p, tmX, tmW1, tmW2, tmO, tmT, tmC, tmY);
}
```
